```python
import torch

def _softmax(x, axis=-1):
    return torch.softmax(x, dim=axis)
def _gelu(x):
    return torch.nn.functional.gelu(x, approximate="tanh")
def _silu(x):
    return torch.nn.functional.silu(x)
def _sigmoid(x):
    return torch.sigmoid(x)
def _layernorm(x, axis=-1, eps=1e-5):
    m = x.mean(dim=axis, keepdim=True)
    v = x.var(dim=axis, keepdim=True, unbiased=False)
    return (x - m) / torch.sqrt(v + eps)
def _scatter_add(tgt, idx, src, axis=0):
    return tgt.clone().index_add_(axis, idx, src)
def _segment_sum(src, seg, n):
    out = torch.zeros((n,) + src.shape[1:], dtype=src.dtype)
    return out.index_add_(0, seg, src)
def _pad(x, pw):
    flat = tuple(v for pair in reversed(pw) for v in pair)
    return torch.nn.functional.pad(x, flat)

kernel_name = 'gated_mix__grouped_kv_mqa__geglu_ffn__prompt'

def setup_inputs():

    _w = (lambda a: (lambda t: t.to(torch.bfloat16) if t.is_floating_point() else t)(torch.as_tensor(a)))
    def _A_setup():
        B, S, D, H = 1, 2048, 512, 32
        Dh = D // H
        return {
            "x": _w((lambda *s: torch.randn(*s, dtype=torch.bfloat16) * 0.05)(B, S, D)),
            "wq": _w((lambda *s: torch.randn(*s, dtype=torch.bfloat16) * 0.8)(D, H * Dh)),
            "wk": _w((lambda *s: torch.randn(*s, dtype=torch.bfloat16) * 0.8)(D, Dh)),
            "wv": _w((lambda *s: torch.randn(*s, dtype=torch.bfloat16) * 0.05)(D, Dh)),
            "wo": _w((lambda *s: torch.randn(*s, dtype=torch.bfloat16) * 0.05)(H * Dh, D)),
        }
    _A_in = _A_setup()

    def _B_setup():
        B, S, D, F = 1, 2048, 512, 1792
        return {
            "x": _w((lambda *s: torch.randn(*s, dtype=torch.bfloat16) * 0.05)(B, S, D)),
            "w_gate": _w((lambda *s: torch.randn(*s, dtype=torch.bfloat16) * 0.05)(D, F)),
            "w_up": _w((lambda *s: torch.randn(*s, dtype=torch.bfloat16) * 0.05)(D, F)),
            "w_down": _w((lambda *s: torch.randn(*s, dtype=torch.bfloat16) * 0.05)(F, D)),
        }
    _B_in = _B_setup()

    return {
        "A_x": _A_in["x"],
        "A_wq": _A_in["wq"],
        "A_wk": _A_in["wk"],
        "A_wv": _A_in["wv"],
        "A_wo": _A_in["wo"],
        "B_x": _B_in["x"],
        "B_w_gate": _B_in["w_gate"],
        "B_w_up": _B_in["w_up"],
        "B_w_down": _B_in["w_down"],
        "gate_w": _w((lambda *s: torch.randn(*s, dtype=torch.bfloat16) * 0.05)(512) * 16.0),
    }

def reference(A_x, A_wq, A_wk, A_wv, A_wo, B_x, B_w_gate, B_w_up, B_w_down, gate_w):
    def _A_ref(x, wq, wk, wv, wo):
        B, S, D = x.shape
        H = 32
        Dh = D // H
        q = (lambda x, *d: x.permute(*d))((x @ wq).reshape(B, S, H, Dh), 0, 2, 1, 3)
        k = x @ wk
        v = x @ wv
        scores = torch.einsum("bhqd,bkd->bhqk", q, k) * (Dh ** -0.5)
        p = _softmax(scores, axis=-1)
        o = torch.einsum("bhqk,bkd->bhqd", p, v)
        return (lambda x, *d: x.permute(*d))(o, 0, 2, 1, 3).reshape(B, S, H * Dh) @ wo

    def _B_ref(x, w_gate, w_up, w_down):
        return (_gelu(x @ w_gate) * (x @ w_up)) @ w_down

    x = A_x
    g = _sigmoid((x * gate_w).sum(-1, keepdims=True))
    a = _A_ref(x, A_wq, A_wk, A_wv, A_wo)
    b = _B_ref(x, B_w_gate, B_w_up, B_w_down)
    return g * a + (1 - g) * b
```

```cpp
#include <cuda_runtime.h>
#include <cuda_bf16.h>
#include <cuda_fp16.h>
#include <cuda.h>
#include <stdint.h>

namespace {

__device__ __align__(1024) unsigned char g_kv[2][8 * 16384];
__device__ __align__(1024) unsigned char g_h[32 * 28 * 8192];
__device__ __align__(1024) unsigned char g_o[32 * 8 * 8192];
__device__ __align__(128) unsigned long long g_kvflag[64];
__device__ __align__(128) unsigned int g_cnt[32 * 3 * 32];
__device__ unsigned int g_epoch[128];
#define TL(i)

struct Maps { CUtensorMap m[7]; };

constexpr int NB = 4;
constexpr uint32_t SM_X = 0;
constexpr uint32_t SM_B = 65536;
constexpr uint32_t SM_KV = SM_B + NB * 16384;
constexpr uint32_t KVS = 20480;
constexpr uint32_t SM_Q = SM_KV + 3 * KVS;
constexpr uint32_t SM_GW = SM_Q + 16384;
constexpr uint32_t SM_G = SM_GW + 1152;
constexpr uint32_t SM_XBAR = SM_G + 256;
constexpr uint32_t SM_BBAR = SM_XBAR + 64;
constexpr uint32_t SM_EBAR = SM_BBAR + 32;
constexpr uint32_t SM_KBAR = SM_EBAR + 32;
constexpr uint32_t SM_KCNT = SM_KBAR + 32;
constexpr uint32_t SM_MAX = SM_KCNT + 16;
constexpr uint32_t SM_TOTAL = SM_MAX + 16;

__device__ __forceinline__ void wg_fence() { asm volatile("wgmma.fence.sync.aligned;" ::: "memory"); }
__device__ __forceinline__ void wg_commit() { asm volatile("wgmma.commit_group.sync.aligned;" ::: "memory"); }
template <int N> __device__ __forceinline__ void wg_wait() { asm volatile("wgmma.wait_group.sync.aligned %0;" ::"n"(N) : "memory"); }
template <int N> __device__ __forceinline__ void regfence(float* d) {
#pragma unroll
  for (int i = 0; i < N; i++) asm volatile("" : "+f"(d[i])::"memory");
}
template <int N> __device__ __forceinline__ void regfence(uint32_t* d) {
#pragma unroll
  for (int i = 0; i < N; i++) asm volatile("" : "+r"(d[i])::"memory");
}
__device__ __forceinline__ uint64_t mkdesc(uint32_t addr, uint32_t lbo, uint32_t sbo, int sw) {
  return (uint64_t)((addr & 0x3FFFF) >> 4) | ((uint64_t)(lbo >> 4) << 16) | ((uint64_t)(sbo >> 4) << 32) | ((uint64_t)sw << 62);
}
__device__ __forceinline__ void mbar_init(uint32_t a, uint32_t c) { asm volatile("mbarrier.init.shared::cta.b64 [%0], %1;" ::"r"(a), "r"(c) : "memory"); }
__device__ __forceinline__ void mbar_expect(uint32_t a, uint32_t b) { asm volatile("mbarrier.arrive.expect_tx.shared::cta.b64 _, [%0], %1;" ::"r"(a), "r"(b) : "memory"); }
__device__ __forceinline__ bool mbar_try(uint32_t a, uint32_t ph) {
  uint32_t ok;
  asm volatile("{\n.reg .pred p;\nmbarrier.try_wait.parity.shared::cta.b64 p, [%1], %2;\nselp.u32 %0, 1, 0, p;\n}" : "=r"(ok) : "r"(a), "r"(ph) : "memory");
  return ok;
}
__device__ __forceinline__ void mbar_wait(uint32_t a, uint32_t ph) {
  if (mbar_try(a, ph)) return;
#pragma unroll 1
  for (int i = 0; i < (1 << 20); i++)
    if (mbar_try(a, ph)) return;
  __trap();
}
__device__ __forceinline__ void bulk_g2s(uint32_t dst, const void* src, uint32_t bytes, uint32_t mbar) {
  asm volatile("cp.async.bulk.shared::cluster.global.mbarrier::complete_tx::bytes [%0], [%1], %2, [%3];" ::"r"(dst), "l"(src), "r"(bytes), "r"(mbar) : "memory");
}
__device__ __forceinline__ void tma_load(uint32_t dst, const CUtensorMap* m, int x, int y, uint32_t mbar) {
  asm volatile("cp.async.bulk.tensor.2d.shared::cluster.global.mbarrier::complete_tx::bytes [%0], [%1, {%2, %3}], [%4];" ::"r"(dst), "l"(m), "r"(x), "r"(y), "r"(mbar) : "memory");
}
__device__ __forceinline__ void tma_store(const CUtensorMap* m, int x, int y, uint32_t src) {
  asm volatile("cp.async.bulk.tensor.2d.global.shared::cta.bulk_group [%0, {%1, %2}], [%3];" ::"l"(m), "r"(x), "r"(y), "r"(src) : "memory");
}
__device__ __forceinline__ void l2_prefetch(const void* p, uint32_t bytes) {
  asm volatile("cp.async.bulk.prefetch.L2.global [%0], %1;" ::"l"(p), "r"(bytes) : "memory");
}
__device__ __forceinline__ void fence_async() { asm volatile("fence.proxy.async.global;" ::: "memory"); }
__device__ __forceinline__ void fence_async_smem() { asm volatile("fence.proxy.async.shared::cta;" ::: "memory"); }
__device__ __forceinline__ void fence_acquire() { asm volatile("fence.acquire.gpu;" ::: "memory"); }
__device__ __forceinline__ bool elect() {
  uint32_t r;
  asm volatile("{\n.reg .pred p;\nelect.sync _|p, 0xffffffff;\nselp.u32 %0, 1, 0, p;\n}" : "=r"(r));
  return r;
}
__device__ __forceinline__ void mbar_arrive(uint32_t a) { asm volatile("mbarrier.arrive.shared::cta.b64 _, [%0];" ::"r"(a) : "memory"); }
__device__ __forceinline__ void bar_sync(int id, int n) { asm volatile("bar.sync %0, %1;" ::"r"(id), "r"(n) : "memory"); }
__device__ __forceinline__ void bar_arrive(int id, int n) { asm volatile("bar.arrive %0, %1;" ::"r"(id), "r"(n) : "memory"); }
__device__ __forceinline__ uint32_t atom_inc_s(uint32_t a) {
  uint32_t r;
  asm volatile("atom.relaxed.cta.shared::cta.inc.u32 %0, [%1], 15;" : "=r"(r) : "r"(a) : "memory");
  return r;
}
__device__ __forceinline__ void red_max_s(uint32_t a, uint32_t v) { asm volatile("red.shared::cta.max.u32 [%0], %1;" ::"r"(a), "r"(v) : "memory"); }
__device__ __forceinline__ uint32_t lds32(uint32_t a) { uint32_t r; asm volatile("ld.shared.u32 %0, [%1];" : "=r"(r) : "r"(a) : "memory"); return r; }
__device__ __forceinline__ float ldsf(uint32_t a) { return __uint_as_float(lds32(a)); }
__device__ __forceinline__ void sts32(uint32_t a, uint32_t v) { asm volatile("st.shared.u32 [%0], %1;" ::"r"(a), "r"(v) : "memory"); }
__device__ __forceinline__ uint4 lds128(uint32_t a) {
  uint4 r;
  asm volatile("ld.shared.v4.u32 {%0,%1,%2,%3}, [%4];" : "=r"(r.x), "=r"(r.y), "=r"(r.z), "=r"(r.w) : "r"(a) : "memory");
  return r;
}
__device__ __forceinline__ void sts128(uint32_t a, uint4 v) { asm volatile("st.shared.v4.u32 [%0], {%1,%2,%3,%4};" ::"r"(a), "r"(v.x), "r"(v.y), "r"(v.z), "r"(v.w) : "memory"); }
__device__ __forceinline__ uint32_t pack_bf16(float lo, float hi) { uint32_t r; asm("cvt.rn.bf16x2.f32 %0, %1, %2;" : "=r"(r) : "f"(hi), "f"(lo)); return r; }
__device__ __forceinline__ uint32_t pack_f16(float lo, float hi) { uint32_t r; asm("cvt.rn.f16x2.f32 %0, %1, %2;" : "=r"(r) : "f"(hi), "f"(lo)); return r; }
__device__ __forceinline__ float bf_lo(uint32_t v) { return __uint_as_float(v << 16); }
__device__ __forceinline__ float bf_hi(uint32_t v) { return __uint_as_float(v & 0xFFFF0000u); }
__device__ __forceinline__ float ex2(float a) { float x; asm("ex2.approx.ftz.f32 %0, %1;" : "=f"(x) : "f"(a)); return x; }
__device__ __forceinline__ void warp_signal(unsigned int* cnt) {
  fence_async();
  __syncwarp();
  if (elect()) asm volatile("red.release.gpu.global.add.u32 [%0], 1;" ::"l"(cnt) : "memory");
}
__device__ __forceinline__ void wait_count(const unsigned int* cnt, uint32_t target) {
#pragma unroll 1
  for (int i = 0; i < (1 << 21); i++) {
    uint32_t v;
    asm volatile("ld.acquire.gpu.global.u32 %0, [%1];" : "=r"(v) : "l"(cnt) : "memory");
    if ((int)(v - target) >= 0) { fence_async(); return; }
  }
  __trap();
}

#define R4(d, i) "+f"(d[i]), "+f"(d[i + 1]), "+f"(d[i + 2]), "+f"(d[i + 3])
#define R8(d, i) R4(d, i), R4(d, i + 4)
#define R32(d, i) R8(d, i), R8(d, i + 8), R8(d, i + 16), R8(d, i + 24)
#define L4 "%0,%1,%2,%3"
#define L8 L4 ",%4,%5,%6,%7"
#define L12 L8 ",%8,%9,%10,%11"
#define L32 L12 ",%12,%13,%14,%15,%16,%17,%18,%19,%20,%21,%22,%23,%24,%25,%26,%27,%28,%29,%30,%31"
#define L64 L32 ",%32,%33,%34,%35,%36,%37,%38,%39,%40,%41,%42,%43,%44,%45,%46,%47,%48,%49,%50,%51,%52,%53,%54,%55,%56,%57,%58,%59,%60,%61,%62,%63"
__device__ __forceinline__ void mma_ss128(float* d, uint64_t da, uint64_t db, int sd) {
  asm volatile("{\n.reg .pred p;\nsetp.ne.b32 p, %66, 0;\nwgmma.mma_async.sync.aligned.m64n128k16.f32.bf16.bf16 {" L64 "}, %64, %65, p, 1, 1, 0, 1;\n}\n"
               : R32(d, 0), R32(d, 32) : "l"(da), "l"(db), "r"(sd));
}
__device__ __forceinline__ void mma_ss16(float* d, uint64_t da, uint64_t db) {
  asm volatile("wgmma.mma_async.sync.aligned.m64n16k16.f32.bf16.bf16 {" L8 "}, %8, %9, 1, 1, 1, 0, 1;\n" : R8(d, 0) : "l"(da), "l"(db));
}
__device__ __forceinline__ void mma_ss8(float* d, uint64_t da, uint64_t db) {
  asm volatile("wgmma.mma_async.sync.aligned.m64n8k16.f32.bf16.bf16 {" L4 "}, %4, %5, 1, 1, 1, 0, 0;\n" : R4(d, 0) : "l"(da), "l"(db));
}
__device__ __forceinline__ void mma_qk_f16(float* d, const uint32_t* a, uint64_t db) {
  asm volatile("wgmma.mma_async.sync.aligned.m64n64k16.f32.f16.f16 {" L32 "}, {%32,%33,%34,%35}, %36, 1, 1, 1, 0;\n"
               : R32(d, 0) : "r"(a[0]), "r"(a[1]), "r"(a[2]), "r"(a[3]), "l"(db));
}
__device__ __forceinline__ void mma_qk_bf16(float* d, const uint32_t* a, uint64_t db) {
  asm volatile("wgmma.mma_async.sync.aligned.m64n64k16.f32.bf16.bf16 {" L32 "}, {%32,%33,%34,%35}, %36, 0, 1, 1, 0;\n"
               : R32(d, 0) : "r"(a[0]), "r"(a[1]), "r"(a[2]), "r"(a[3]), "l"(db));
}
__device__ __forceinline__ void mma_pv(float* d, const uint32_t* a, uint64_t db) {
  asm volatile("wgmma.mma_async.sync.aligned.m64n24k16.f32.bf16.bf16 {" L12 "}, {%12,%13,%14,%15}, %16, 1, 1, 1, 1;\n"
               : R8(d, 0), R4(d, 8) : "r"(a[0]), "r"(a[1]), "r"(a[2]), "r"(a[3]), "l"(db));
}

__device__ __forceinline__ uint32_t exp_mufu(float a, float b) { return pack_bf16(ex2(a), ex2(b)); }
constexpr float EXP_MAGIC = 446.0f + 0.00390625f - 0.5860f;
constexpr uint32_t POLY_MASK = 0x7777u;
__device__ __forceinline__ uint32_t exp_soft(float t0, float t1, uint32_t cor) {
  uint32_t y = __byte_perm(__float_as_uint(t0), __float_as_uint(t1), 0x6521);
  uint32_t u, r;
  asm("lop3.b32 %0, %1, 0x007F007F, %2, 0xEA;" : "=r"(u) : "r"(y), "r"(cor));
  uint32_t e = y - u;
  asm("fma.rn.bf16x2 %0, %1, %2, %3;" : "=r"(r) : "r"(y), "r"(u), "r"(e));
  return r;
}
constexpr float QSCALE = 0.25f * 1.4426950408889634f;

template <bool FAST>
__device__ __forceinline__ void attn_pass(uint32_t sb, int pass, uint32_t& slot, uint32_t& ph, const unsigned char* kvsrc,
                                          uint32_t cor, unsigned char* odst) {
  const int tid = threadIdx.x, lane = tid & 31;
  uint32_t q[4], p[16];
  float o[12], s[32];
  float m0 = -INFINITY, m1 = -INFINITY;
  {
    uint4 v = lds128(sb + SM_Q + pass * 8192 + tid * 16);
    q[0] = v.x, q[1] = v.y, q[2] = v.z, q[3] = v.w;
    if (FAST) {
#pragma unroll
      for (int i = 0; i < 4; i++) q[i] = pack_f16(bf_lo(q[i]) * QSCALE, bf_hi(q[i]) * QSCALE);
    }
  }
#pragma unroll
  for (int i = 0; i < 12; i++) o[i] = 0.f;
#pragma unroll
  for (int j = 0; j < 32; j++) s[j] = (FAST && ((POLY_MASK >> (j / 2)) & 1)) ? EXP_MAGIC : 0.f;
  regfence<12>(o); regfence<32>(s); regfence<4>(q);
  uint32_t prev = 0;
  auto release = [&](uint32_t sl, int j) {
    if (j < 13 && elect()) {
      if (atom_inc_s(sb + SM_KCNT + sl * 4) == 15) {
        mbar_expect(sb + SM_KBAR + sl * 8, 16384);
        bulk_g2s(sb + SM_KV + sl * KVS, kvsrc + ((j + 3) & 7) * 16384, 16384, sb + SM_KBAR + sl * 8);
      }
    }
    __syncwarp();
  };
#pragma unroll 1
  for (int c = 0; c < 8; c++) {
    mbar_wait(sb + SM_KBAR + slot * 8, ph);
    const uint64_t dk = mkdesc(sb + SM_KV + slot * KVS, 128, 256, 0);
    const uint64_t dv = mkdesc(sb + SM_KV + slot * KVS + 8192, 128, 4096, 0);
#pragma unroll
    for (int h = 0; h < 4; h++) {
      wg_fence();
      if (FAST) mma_qk_f16(s, q, dk + h * 128); else mma_qk_bf16(s, q, dk + h * 128);
      wg_commit();
      wg_wait<0>();
      regfence<32>(s);
      if (h == 0 && c > 0) release(prev, pass * 8 + c - 1);
      if (FAST) {
#pragma unroll
        for (int j = 0; j < 16; j++)
          p[j] = ((POLY_MASK >> j) & 1) ? exp_soft(s[2 * j], s[2 * j + 1], cor) : exp_mufu(s[2 * j], s[2 * j + 1]);
      } else {
        regfence<12>(o);
        float n0 = m0, n1 = m1;
#pragma unroll
        for (int j = 0; j < 16; j++) {
          uint32_t r = pack_bf16(s[2 * j], s[2 * j + 1]);
          s[2 * j] = bf_lo(r), s[2 * j + 1] = bf_hi(r);
          if (j & 1) n1 = fmaxf(n1, fmaxf(s[2 * j], s[2 * j + 1])); else n0 = fmaxf(n0, fmaxf(s[2 * j], s[2 * j + 1]));
        }
        n0 = fmaxf(n0, __shfl_xor_sync(~0u, n0, 1)); n0 = fmaxf(n0, __shfl_xor_sync(~0u, n0, 2));
        n1 = fmaxf(n1, __shfl_xor_sync(~0u, n1, 1)); n1 = fmaxf(n1, __shfl_xor_sync(~0u, n1, 2));
        const float a0 = ex2((m0 - n0) * QSCALE), a1 = ex2((m1 - n1) * QSCALE);
        m0 = n0, m1 = n1;
#pragma unroll
        for (int i = 0; i < 12; i++) o[i] *= (i & 2) ? a1 : a0;
#pragma unroll
        for (int j = 0; j < 16; j++) {
          const float m = (j & 1) ? m1 : m0;
          p[j] = exp_mufu((s[2 * j] - m) * QSCALE, (s[2 * j + 1] - m) * QSCALE);
        }
        regfence<12>(o);
      }
      wg_fence();
#pragma unroll
      for (int i = 0; i < 4; i++) mma_pv(o, p + 4 * i, dv + (h * 4 + i) * 16);
      wg_commit();
    }
    prev = slot;
    if (++slot == 3) slot = 0, ph ^= 1;
  }
  wg_wait<0>();
  regfence<12>(o); regfence<32>(s);
  release(prev, pass * 8 + 7);
  const int row = ((tid >> 5) & 3) * 16 + (lane >> 2);
  const float l0 = __shfl_sync(~0u, o[8], lane & ~3), l1 = __shfl_sync(~0u, o[10], lane & ~3);
  const float r0 = __fdividef(ldsf(sb + SM_G + row * 4), l0), r1 = __fdividef(ldsf(sb + SM_G + row * 4 + 32), l1);
  uint32_t* op = (uint32_t*)odst;
  op[0] = pack_bf16(o[0] * r0, o[1] * r0);
  op[32] = pack_bf16(o[2] * r1, o[3] * r1);
  op[256] = pack_bf16(o[4] * r0, o[5] * r0);
  op[288] = pack_bf16(o[6] * r1, o[7] * r1);
}

struct Src { const CUtensorMap *m0, *m1; int x0, x1, y; uint32_t bytes; const unsigned char* a; };
__device__ __forceinline__ void issue_stage(uint32_t sb, int slot, const Src& s) {
  const uint32_t bar = sb + SM_BBAR + slot * 8, dst = sb + SM_B + slot * 16384;
  mbar_expect(bar, s.bytes);
  tma_load(dst, s.m0, s.x0, s.y, bar);
  tma_load(dst + 8192, s.m1, s.x1, s.y, bar);
  if (s.a) bulk_g2s(sb + SM_X + slot * 8192, s.a, 8192, bar);
}

__global__ void __launch_bounds__(640, 1)
fused_kernel(const __grid_constant__ Maps maps, const __nv_bfloat16* __restrict__ wk, const __nv_bfloat16* __restrict__ wv,
             const __nv_bfloat16* __restrict__ gw, const unsigned char* __restrict__ pf_gate, const unsigned char* __restrict__ pf_up,
             const unsigned char* __restrict__ pf_down, const unsigned char* __restrict__ pf_wo,
             const unsigned char* __restrict__ pf_x, const unsigned char* __restrict__ pf_wq, uint32_t cor) {
  extern __shared__ __align__(1024) unsigned char smem[];
  const uint32_t sb = (uint32_t)__cvta_generic_to_shared(smem);
  const int tid = threadIdx.x, wg = __shfl_sync(~0u, tid >> 7, 0), warp = (tid >> 5) & 3, lane = tid & 31;
  const int T = blockIdx.x >> 2, c = blockIdx.x & 3;
  if (tid == 512) {
    for (int i = 0; i < 8; i++) mbar_init(sb + SM_XBAR + 8 * i, 1);
    for (int i = 0; i < NB; i++) mbar_init(sb + SM_BBAR + 8 * i, 1), mbar_init(sb + SM_EBAR + 8 * i, 4);
    for (int i = 0; i < 3; i++) mbar_init(sb + SM_KBAR + 8 * i, 1);
    asm volatile("fence.mbarrier_init.release.cluster;" ::: "memory");
    for (int i = 0; i < 8; i++) {
      mbar_expect(sb + SM_XBAR + 8 * i, 8192);
      tma_load(sb + SM_X + i * 8192, &maps.m[0], 64 * i, 64 * T, sb + SM_XBAR + 8 * i);
    }
    for (int i = 0; i < NB; i++) issue_stage(sb, i, Src{&maps.m[1], &maps.m[1], 128 * c, 128 * c + 64, 64 * i, 16384, nullptr});
  } else if (tid == 608) {
    l2_prefetch(pf_x + blockIdx.x * 16384, 16384);
    l2_prefetch(pf_wq + blockIdx.x * 4096, 4096);
  } else if (tid >= 544 && tid < 552) {
    sts32(sb + SM_KCNT + (tid - 544) * 4, 0);
  } else if (tid >= 576 && tid < 581) {
    asm volatile("prefetch.tensormap [%0];" ::"l"(&maps.m[tid - 574]) : "memory");
  }
  const uint32_t epoch = g_epoch[blockIdx.x] + 1;
  if (wg == 0 && c < 2) {
    const uint4* src = (const uint4*)(c == 0 ? wk : wv);
    uint4 v[8];
#pragma unroll
    for (int i = 0; i < 8; i++) v[i] = __ldg(src + i * 128 + tid);
#pragma unroll
    for (int i = 0; i < 8; i++) sts128(sb + SM_KV + (tid & 1) * 8192 + (i * 64 + (tid >> 1)) * 16, v[i]);
    fence_async_smem();
  } else if (wg == 1) {
    if (tid < 192) sts128(sb + SM_GW + (tid - 128) * 16, __ldg((const uint4*)gw + tid - 128));
    fence_async_smem();
  } else if (wg == 2 || wg == 3) {
#pragma unroll
    for (int i = 0; i < 3; i++) sts128(sb + SM_KV + i * KVS + 16384 + (tid - 256) * 16, make_uint4(0x3F80u, 0, 0, 0));
    fence_async_smem();
  }
  __syncthreads();
  if (wg == 3) { TL(26); mbar_wait(sb + SM_XBAR, 0); TL(27); mbar_wait(sb + SM_XBAR + 56, 0); TL(28); }
  const uint64_t dx = mkdesc(sb + SM_X, 16, 1024, 1);

  if (wg < 4) {
    if (wg == 0 && c < 2) {
      float a[8];
#pragma unroll
      for (int i = 0; i < 8; i++) a[i] = 0.f;
      const uint64_t dw = mkdesc(sb + SM_KV, 128, 8192, 0);
      regfence<8>(a);
#pragma unroll 1
      for (int kb = 0; kb < 8; kb++) {
        mbar_wait(sb + SM_XBAR + kb * 8, 0);
        wg_fence();
#pragma unroll
        for (int k = 0; k < 4; k++) mma_ss16(a, dx + kb * 512 + k * 2, dw + (kb * 4 + k) * 16);
        wg_commit();
      }
      wg_wait<0>();
      regfence<8>(a);
      TL(0);
      const uint32_t st = sb + SM_KV + KVS;
      const uint32_t ad = st + (warp * 16 + (lane >> 2)) * 32 + (lane & 3) * 4;
      sts32(ad, pack_bf16(a[0], a[1]));
      sts32(ad + 256, pack_bf16(a[2], a[3]));
      sts32(ad + 16, pack_bf16(a[4], a[5]));
      sts32(ad + 272, pack_bf16(a[6], a[7]));
      bar_sync(5, 128);
      const int r = tid >> 1, hb = tid & 1, j = r >> 1, kk = (j & 3) * 64 + 2 * T + (r & 1);
      const uint4 v = lds128(st + tid * 16);
      if (c == 0) {
        uint4 w = make_uint4(0, 0, 0, 0);
        if (r >= 2) w = lds128(st + tid * 16 - 64);
        uint4 d;
        d.x = pack_f16(bf_lo(v.x) - bf_lo(w.x), bf_hi(v.x) - bf_hi(w.x));
        d.y = pack_f16(bf_lo(v.y) - bf_lo(w.y), bf_hi(v.y) - bf_hi(w.y));
        d.z = pack_f16(bf_lo(v.z) - bf_lo(w.z), bf_hi(v.z) - bf_hi(w.z));
        d.w = pack_f16(bf_lo(v.w) - bf_lo(w.w), bf_hi(v.w) - bf_hi(w.w));
        const int off = (j >> 2) * 16384 + (kk >> 3) * 256 + hb * 128 + (kk & 7) * 16;
        *(uint4*)(g_kv[0] + off) = d;
        *(uint4*)(g_kv[1] + off) = v;
      } else {
        const int off = (j >> 2) * 16384 + 8192 + hb * 4096 + kk * 16;
        *(uint4*)(g_kv[0] + off) = v;
        *(uint4*)(g_kv[1] + off) = v;
      }
      float n2 = bf_lo(v.x) * bf_lo(v.x) + bf_hi(v.x) * bf_hi(v.x) + bf_lo(v.y) * bf_lo(v.y) + bf_hi(v.y) * bf_hi(v.y) +
                 bf_lo(v.z) * bf_lo(v.z) + bf_hi(v.z) * bf_hi(v.z) + bf_lo(v.w) * bf_lo(v.w) + bf_hi(v.w) * bf_hi(v.w);
      n2 += __shfl_xor_sync(~0u, n2, 1);
      const uint32_t mx = __reduce_max_sync(~0u, __float_as_uint(n2) & 0x7FFFFFFFu);
      if (lane == 0) red_max_s(sb + SM_MAX + 12, mx);
      fence_async();
      bar_sync(5, 128);
      if (tid == 0) {
        const unsigned long long f = ((unsigned long long)epoch << 32) | lds32(sb + SM_MAX + 12);
        asm volatile("st.release.gpu.global.u64 [%0], %1;" ::"l"(g_kvflag + 2 * T + c), "l"(f) : "memory");
      }
      TL(1);
    } else if (wg == 1) {
      float a[4] = {0.f, 0.f, 0.f, 0.f};
      const uint64_t dw = mkdesc(sb + SM_GW, 16, 128, 0);
      regfence<4>(a);
#pragma unroll 1
      for (int kb = 0; kb < 8; kb++) {
        mbar_wait(sb + SM_XBAR + kb * 8, 0);
        wg_fence();
#pragma unroll
        for (int k = 0; k < 4; k++) mma_ss8(a, dx + kb * 512 + k * 2, dw + (kb * 4 + k) * 2);
        wg_commit();
      }
      if (tid == 128) {
        l2_prefetch(pf_gate + blockIdx.x * 14336, 14336);
        l2_prefetch(pf_up + blockIdx.x * 14336, 14336);
        l2_prefetch(pf_down + blockIdx.x * 14336, 14336);
        l2_prefetch(pf_wo + blockIdx.x * 4096, 4096);
      }
      __syncwarp();
      wg_wait<0>();
      regfence<4>(a);
      if ((lane & 3) == 0) {
        const uint32_t ad = sb + SM_G + (warp * 16 + (lane >> 2)) * 4;
        sts32(ad, __float_as_uint(1.f / (1.f + __expf(-a[0]))));
        sts32(ad + 32, __float_as_uint(1.f / (1.f + __expf(-a[2]))));
      }
      TL(2);
    }
    if (wg < 2) bar_arrive(3, 384);
    bar_sync(1, 640);
    {
      float n0 = 0.f, n1 = 0.f;
#pragma unroll
      for (int p = 0; p < 2; p++) {
        const uint4 v = lds128(sb + SM_Q + p * 8192 + tid * 16);
        float a = bf_lo(v.x) * bf_lo(v.x) + bf_hi(v.x) * bf_hi(v.x) + bf_lo(v.z) * bf_lo(v.z) + bf_hi(v.z) * bf_hi(v.z);
        float b = bf_lo(v.y) * bf_lo(v.y) + bf_hi(v.y) * bf_hi(v.y) + bf_lo(v.w) * bf_lo(v.w) + bf_hi(v.w) * bf_hi(v.w);
        a += __shfl_xor_sync(~0u, a, 1); a += __shfl_xor_sync(~0u, a, 2);
        b += __shfl_xor_sync(~0u, b, 1); b += __shfl_xor_sync(~0u, b, 2);
        if (p == 0) n0 = a, n1 = b;
        else n0 = __uint_as_float(max(__float_as_uint(n0) & 0x7FFFFFFFu, __float_as_uint(a) & 0x7FFFFFFFu)),
             n1 = __uint_as_float(max(__float_as_uint(n1) & 0x7FFFFFFFu, __float_as_uint(b) & 0x7FFFFFFFu));
      }
      const uint32_t mx = __reduce_max_sync(~0u, max(__float_as_uint(n0), __float_as_uint(n1)));
      if (lane == 0) red_max_s(sb + SM_MAX, mx);
    }
    if (tid >= 256 && tid < 288) {
      unsigned long long fk, fv;
      bool ok = false;
#pragma unroll 1
      for (int i = 0; i < (1 << 21) && !ok; i++) {
        asm volatile("ld.relaxed.gpu.global.v2.u64 {%0, %1}, [%2];" : "=l"(fk), "=l"(fv) : "l"(g_kvflag + 2 * lane) : "memory");
        ok = __all_sync(~0u, (uint32_t)(fk >> 32) == epoch && (uint32_t)(fv >> 32) == epoch);
      }
      if (!ok) __trap();
      fence_acquire();
      fence_async();
      __syncwarp();
      if (lane < 3) {
        mbar_expect(sb + SM_KBAR + lane * 8, 16384);
        bulk_g2s(sb + SM_KV + lane * KVS, g_kv[0] + lane * 16384, 16384, sb + SM_KBAR + lane * 8);
      }
      const uint32_t km = __reduce_max_sync(~0u, (uint32_t)fk), vm = __reduce_max_sync(~0u, (uint32_t)fv);
      if (lane == 0) sts32(sb + SM_MAX + 4, km), sts32(sb + SM_MAX + 8, vm);
      TL(3);
    }
    bar_sync(2, 512);
    const float qm = ldsf(sb + SM_MAX), km = ldsf(sb + SM_MAX + 4), vm = ldsf(sb + SM_MAX + 8);
    const bool fast = qm * km * (QSCALE * QSCALE) <= 48.f * 48.f && qm <= 1048576.f && km <= 1048576.f && vm <= 1e30f;
    unsigned char* odst = g_o + (T * 8 + 2 * c) * 8192 + wg * 2048 + warp * 256 + lane * 4;
    unsigned int* ocnt = g_cnt + (T * 3 + 1) * 32;
    uint32_t slot = 0, ph = 0;
    if (fast) {
#pragma unroll 1
      for (int pass = 0; pass < 2; pass++) {
        attn_pass<true>(sb, pass, slot, ph, g_kv[0], cor, odst + pass * 8192);
        warp_signal(ocnt + pass * 32);
        TL(4 + wg * 2 + pass);
      }
    } else {
      if (tid < 3) {
        mbar_wait(sb + SM_KBAR + tid * 8, 0);
        mbar_expect(sb + SM_KBAR + tid * 8, 16384);
        bulk_g2s(sb + SM_KV + tid * KVS, g_kv[1] + tid * 16384, 16384, sb + SM_KBAR + tid * 8);
      }
      bar_sync(2, 512);
      ph = 1;
#pragma unroll 1
      for (int pass = 0; pass < 2; pass++) {
        attn_pass<false>(sb, pass, slot, ph, g_kv[1], cor, odst + pass * 8192);
        warp_signal(ocnt + pass * 32);
      }
    }
  } else {
    float acc[64];
    const int wu = __shfl_sync(~0u, warp, 0);
    auto release = [&](int sl, uint32_t ph, bool refill, const Src& src) {
      if (elect()) mbar_arrive(sb + SM_EBAR + sl * 8);
      if (refill && wu == sl) {
        mbar_wait(sb + SM_EBAR + sl * 8, ph);
        if (elect()) issue_stage(sb, sl, src);
      }
    };
    auto stage = [&](int sl, uint32_t ph, uint64_t da, int ka, bool first) {
      mbar_wait(sb + SM_BBAR + sl * 8, ph);
      const uint64_t db = mkdesc(sb + SM_B + sl * 16384, 8192, 1024, 1);
      wg_fence();
      mma_ss128(acc, da, db, !first);
#pragma unroll
      for (int k = 1; k < 4; k++) mma_ss128(acc, da + k * ka, db + k * 128, 1);
      wg_commit();
    };
#pragma unroll 1
    for (int u = 0; u < 8; u++) {
      Src cur, nxt;
      if (u == 0) cur = Src{&maps.m[1], &maps.m[1], 128 * c, 128 * c + 64, 0, 16384, nullptr};
      else cur = Src{&maps.m[2], &maps.m[3], 448 * c + 64 * u - 64, 448 * c + 64 * u - 64, 0, 16384, nullptr};
      if (u == 7) nxt = Src{&maps.m[4], &maps.m[4], 128 * c, 128 * c + 64, 0, 24576, nullptr};
      else nxt = Src{&maps.m[2], &maps.m[3], 448 * c + 64 * u, 448 * c + 64 * u, 0, 16384, nullptr};
#pragma unroll
      for (int kb = 0; kb < 9; kb++) {
        if (kb < 8) {
          if (u == 0) mbar_wait(sb + SM_XBAR + kb * 8, 0);
          stage(kb & 3, kb >> 2, dx + kb * 512, 2, kb == 0);
        }
        if (kb > 0) {
          if (kb < 8) wg_wait<1>(); else wg_wait<0>();
          Src t = kb < 5 ? cur : nxt;
          t.y = ((kb + 3) & 7) * 64;
          release((kb - 1) & 3, (kb - 1) >> 2, true, t);
        }
      }
      regfence<64>(acc);
      if (u == 0) {
#pragma unroll
        for (int h = 0; h < 8; h++)
          sts128(sb + SM_Q + h * 2048 + (tid - 512) * 16,
                 make_uint4(pack_bf16(acc[8 * h], acc[8 * h + 1]), pack_bf16(acc[8 * h + 2], acc[8 * h + 3]),
                            pack_bf16(acc[8 * h + 4], acc[8 * h + 5]), pack_bf16(acc[8 * h + 6], acc[8 * h + 7])));
        bar_arrive(1, 640);
      } else {
        uint32_t* hp = (uint32_t*)(g_h + (T * 28 + c * 7 + u - 1) * 8192 + warp * 256) + lane;
#pragma unroll
        for (int j = 0; j < 16; j++) {
          float h[2];
#pragma unroll
          for (int e = 0; e < 2; e++) {
            const float x = acc[2 * j + e];
            float t;
            asm("tanh.approx.f32 %0, %1;" : "=f"(t) : "f"(x * fmaf(x * x, 0.044715f * 0.7978845608028654f, 0.7978845608028654f)));
            const float w = 0.5f * x * acc[32 + 2 * j + e];
            h[e] = fmaf(w, t, w);
          }
          hp[(j >> 1) * 256 + (j & 1) * 32] = pack_bf16(h[0], h[1]);
        }
      }
      TL(12 + u);
    }
    warp_signal(g_cnt + T * 96);
    bar_sync(3, 384);
    const unsigned char* hsrc = g_h + T * 28 * 8192;
    if (wu == 0 && elect()) {
      wait_count(g_cnt + T * 96, epoch * 16);
#pragma unroll
      for (int j = 0; j < NB; j++) bulk_g2s(sb + SM_X + j * 8192, hsrc + j * 8192, 8192, sb + SM_BBAR + j * 8);
    }
    __syncwarp();
    TL(20);
    const uint64_t da0 = mkdesc(sb + SM_X, 1024, 128, 0);
#pragma unroll 1
    for (int g = 0; g < 7; g++) {
#pragma unroll
      for (int j = 0; j < 4; j++) {
        stage(j, g & 1, da0 + j * 512, 128, g == 0 && j == 0);
        if (j > 0 || g > 0) {
          wg_wait<1>();
          const int n = 4 * g + j + 3;
          Src t{&maps.m[4], &maps.m[4], 128 * c, 128 * c + 64, n * 64, 24576, hsrc + n * 8192};
          if (j > 0 && g == 6) t.m0 = t.m1 = &maps.m[5], t.y = (j - 1) * 128, t.a = nullptr;
          release((j + 3) & 3, (j == 0 ? g + 1 : g) & 1, true, t);
        }
      }
    }
    wg_wait<0>();
    regfence<64>(acc);
    release(3, 0, true, Src{&maps.m[5], &maps.m[5], 128 * c, 128 * c + 64, 384, 24576, nullptr});
    TL(21);
    {
      const uint32_t ad = sb + SM_G + (warp * 16 + (lane >> 2)) * 4;
      const float s0 = 1.f - ldsf(ad), s1 = 1.f - ldsf(ad + 32);
#pragma unroll
      for (int j = 0; j < 64; j++) acc[j] *= (j & 2) ? s1 : s0;
      regfence<64>(acc);
    }
    bar_sync(4, 128);
#pragma unroll 1
    for (int p = 0; p < 2; p++) {
      if (wu == 0 && elect()) {
        wait_count(g_cnt + T * 96 + 32 + p * 32, epoch * 64);
#pragma unroll
        for (int j = 0; j < 4; j++)
          bulk_g2s(sb + SM_X + (p * 4 + j) * 8192, g_o + (T * 8 + 2 * j + p) * 8192, 8192, sb + SM_BBAR + j * 8);
      }
      __syncwarp();
      TL(22 + p);
#pragma unroll
      for (int j = 0; j < 5; j++) {
        if (j < 4) stage(j, p ^ 1, da0 + (p * 4 + j) * 512, 128, false);
        if (j > 0) {
          if (j < 4) wg_wait<1>(); else wg_wait<0>();
          release(j - 1, 1, p == 0, Src{&maps.m[5], &maps.m[5], 128 * c, 128 * c + 64, (j - 1) * 128 + 64, 24576, nullptr});
        }
      }
    }
    regfence<64>(acc);
    TL(24);
    {
      const int r = (lane & 7) + (lane & 8);
      const uint32_t wb = sb + SM_Q + warp * 4096;
#pragma unroll
      for (int j = 0; j < 8; j++) {
        const int blk = 2 * j + (lane >> 4);
        const uint32_t ad = wb + (blk >> 3) * 2048 + r * 128 + (((blk & 7) ^ (r & 7)) << 4);
        asm volatile("stmatrix.sync.aligned.m8n8.x4.shared.b16 [%0], {%1,%2,%3,%4};" ::"r"(ad),
                     "r"(pack_bf16(acc[8 * j], acc[8 * j + 1])), "r"(pack_bf16(acc[8 * j + 2], acc[8 * j + 3])),
                     "r"(pack_bf16(acc[8 * j + 4], acc[8 * j + 5])), "r"(pack_bf16(acc[8 * j + 6], acc[8 * j + 7])) : "memory");
      }
      fence_async_smem();
      __syncwarp();
      if (lane == 0) {
        tma_store(&maps.m[6], 128 * c, 64 * T + 16 * warp, wb);
        tma_store(&maps.m[6], 128 * c + 64, 64 * T + 16 * warp, wb + 2048);
        asm volatile("cp.async.bulk.commit_group;" ::: "memory");
        if (warp == 0) g_epoch[blockIdx.x] = epoch;
        asm volatile("cp.async.bulk.wait_group.read 0;" ::: "memory");
      }
    }
    TL(25);
  }
}

typedef CUresult (*EncodeFn)(CUtensorMap*, CUtensorMapDataType, cuuint32_t, void*, const cuuint64_t*, const cuuint64_t*,
                             const cuuint32_t*, const cuuint32_t*, CUtensorMapInterleave, CUtensorMapSwizzle,
                             CUtensorMapL2promotion, CUtensorMapFloatOOBfill);

void make_map(EncodeFn fn, CUtensorMap* m, void* p, int rows, int cols, int box_rows) {
  cuuint64_t dims[2] = {(cuuint64_t)cols, (cuuint64_t)rows};
  cuuint64_t strides[1] = {(cuuint64_t)cols * 2};
  cuuint32_t box[2] = {64, (cuuint32_t)box_rows};
  cuuint32_t es[2] = {1, 1};
  fn(m, CU_TENSOR_MAP_DATA_TYPE_BFLOAT16, 2, p, dims, strides, box, es, CU_TENSOR_MAP_INTERLEAVE_NONE,
     CU_TENSOR_MAP_SWIZZLE_128B, CU_TENSOR_MAP_L2_PROMOTION_L2_128B, CU_TENSOR_MAP_FLOAT_OOB_FILL_NONE);
}

}

extern "C" void kernel_launch(void* const* d_in, const int* in_sizes, int n_in, void* d_out, int out_size) {
  static EncodeFn fn = nullptr;
  if (!fn) {
    void* p = nullptr;
    cudaDriverEntryPointQueryResult st;
    cudaGetDriverEntryPoint("cuTensorMapEncodeTiled", &p, cudaEnableDefault, &st);
    fn = (EncodeFn)p;
    cudaFuncSetAttribute(fused_kernel, cudaFuncAttributeMaxDynamicSharedMemorySize, SM_TOTAL);
  }
  Maps maps;
  make_map(fn, &maps.m[0], d_in[0], 2048, 512, 64);
  make_map(fn, &maps.m[1], d_in[1], 512, 512, 64);
  make_map(fn, &maps.m[2], d_in[6], 512, 1792, 64);
  make_map(fn, &maps.m[3], d_in[7], 512, 1792, 64);
  make_map(fn, &maps.m[4], d_in[8], 1792, 512, 64);
  make_map(fn, &maps.m[5], d_in[4], 512, 512, 64);
  make_map(fn, &maps.m[6], d_out, 2048, 512, 16);
  fused_kernel<<<128, 640, SM_TOTAL>>>(maps, (const __nv_bfloat16*)d_in[2], (const __nv_bfloat16*)d_in[3],
                                       (const __nv_bfloat16*)d_in[9], (const unsigned char*)d_in[6], (const unsigned char*)d_in[7],
                                       (const unsigned char*)d_in[8], (const unsigned char*)d_in[4],
                                       (const unsigned char*)d_in[0], (const unsigned char*)d_in[1], 0x9F809F80u);
}
```

```cpp
#include <cuda_runtime.h>
#include <cuda_bf16.h>
#include <cuda_fp16.h>
#include <cuda.h>
#include <stdint.h>

namespace {

__device__ __align__(1024) unsigned char g_kv[2][8 * 16384];
__device__ __align__(1024) unsigned char g_h[32 * 28 * 8192];
__device__ __align__(1024) unsigned char g_o[32 * 8 * 8192];
__device__ __align__(128) unsigned long long g_kvflag[64];
__device__ __align__(128) unsigned int g_cnt[32 * 3 * 32];
__device__ unsigned int g_epoch[128];
#define TL(i)

struct Maps { CUtensorMap m[7]; };

constexpr int NB = 4;
constexpr uint32_t SM_X = 0;
constexpr uint32_t SM_B = 65536;
constexpr uint32_t SM_KV = SM_B + NB * 16384;
constexpr uint32_t KVS = 20480;
constexpr uint32_t SM_Q = SM_KV + 3 * KVS;
constexpr uint32_t SM_GW = SM_Q + 16384;
constexpr uint32_t SM_G = SM_GW + 1152;
constexpr uint32_t SM_XBAR = SM_G + 256;
constexpr uint32_t SM_BBAR = SM_XBAR + 64;
constexpr uint32_t SM_EBAR = SM_BBAR + 32;
constexpr uint32_t SM_KBAR = SM_EBAR + 32;
constexpr uint32_t SM_KCNT = SM_KBAR + 32;
constexpr uint32_t SM_MAX = SM_KCNT + 16;
constexpr uint32_t SM_TOTAL = SM_MAX + 16;

__device__ __forceinline__ void wg_fence() { asm volatile("wgmma.fence.sync.aligned;" ::: "memory"); }
__device__ __forceinline__ void wg_commit() { asm volatile("wgmma.commit_group.sync.aligned;" ::: "memory"); }
template <int N> __device__ __forceinline__ void wg_wait() { asm volatile("wgmma.wait_group.sync.aligned %0;" ::"n"(N) : "memory"); }
template <int N> __device__ __forceinline__ void regfence(float* d) {
#pragma unroll
  for (int i = 0; i < N; i++) asm volatile("" : "+f"(d[i])::"memory");
}
template <int N> __device__ __forceinline__ void regfence(uint32_t* d) {
#pragma unroll
  for (int i = 0; i < N; i++) asm volatile("" : "+r"(d[i])::"memory");
}
__device__ __forceinline__ uint64_t mkdesc(uint32_t addr, uint32_t lbo, uint32_t sbo, int sw) {
  return (uint64_t)((addr & 0x3FFFF) >> 4) | ((uint64_t)(lbo >> 4) << 16) | ((uint64_t)(sbo >> 4) << 32) | ((uint64_t)sw << 62);
}
__device__ __forceinline__ void mbar_init(uint32_t a, uint32_t c) { asm volatile("mbarrier.init.shared::cta.b64 [%0], %1;" ::"r"(a), "r"(c) : "memory"); }
__device__ __forceinline__ void mbar_expect(uint32_t a, uint32_t b) { asm volatile("mbarrier.arrive.expect_tx.shared::cta.b64 _, [%0], %1;" ::"r"(a), "r"(b) : "memory"); }
__device__ __forceinline__ bool mbar_try(uint32_t a, uint32_t ph) {
  uint32_t ok;
  asm volatile("{\n.reg .pred p;\nmbarrier.try_wait.parity.shared::cta.b64 p, [%1], %2;\nselp.u32 %0, 1, 0, p;\n}" : "=r"(ok) : "r"(a), "r"(ph) : "memory");
  return ok;
}
__device__ __forceinline__ void mbar_wait(uint32_t a, uint32_t ph) {
  if (mbar_try(a, ph)) return;
#pragma unroll 1
  for (int i = 0; i < (1 << 20); i++)
    if (mbar_try(a, ph)) return;
  __trap();
}
__device__ __forceinline__ void bulk_g2s(uint32_t dst, const void* src, uint32_t bytes, uint32_t mbar) {
  asm volatile("cp.async.bulk.shared::cluster.global.mbarrier::complete_tx::bytes [%0], [%1], %2, [%3];" ::"r"(dst), "l"(src), "r"(bytes), "r"(mbar) : "memory");
}
__device__ __forceinline__ void tma_load(uint32_t dst, const CUtensorMap* m, int x, int y, uint32_t mbar) {
  asm volatile("cp.async.bulk.tensor.2d.shared::cluster.global.mbarrier::complete_tx::bytes [%0], [%1, {%2, %3}], [%4];" ::"r"(dst), "l"(m), "r"(x), "r"(y), "r"(mbar) : "memory");
}
__device__ __forceinline__ void tma_store(const CUtensorMap* m, int x, int y, uint32_t src) {
  asm volatile("cp.async.bulk.tensor.2d.global.shared::cta.bulk_group [%0, {%1, %2}], [%3];" ::"l"(m), "r"(x), "r"(y), "r"(src) : "memory");
}
__device__ __forceinline__ void l2_prefetch(const void* p, uint32_t bytes) {
  asm volatile("cp.async.bulk.prefetch.L2.global [%0], %1;" ::"l"(p), "r"(bytes) : "memory");
}
__device__ __forceinline__ void fence_async() { asm volatile("fence.proxy.async.global;" ::: "memory"); }
__device__ __forceinline__ void fence_async_smem() { asm volatile("fence.proxy.async.shared::cta;" ::: "memory"); }
__device__ __forceinline__ void fence_acquire() { asm volatile("fence.acquire.gpu;" ::: "memory"); }
__device__ __forceinline__ bool elect() {
  uint32_t r;
  asm volatile("{\n.reg .pred p;\nelect.sync _|p, 0xffffffff;\nselp.u32 %0, 1, 0, p;\n}" : "=r"(r));
  return r;
}
__device__ __forceinline__ void mbar_arrive(uint32_t a) { asm volatile("mbarrier.arrive.shared::cta.b64 _, [%0];" ::"r"(a) : "memory"); }
__device__ __forceinline__ void bar_sync(int id, int n) { asm volatile("bar.sync %0, %1;" ::"r"(id), "r"(n) : "memory"); }
__device__ __forceinline__ void bar_arrive(int id, int n) { asm volatile("bar.arrive %0, %1;" ::"r"(id), "r"(n) : "memory"); }
__device__ __forceinline__ uint32_t atom_inc_s(uint32_t a) {
  uint32_t r;
  asm volatile("atom.relaxed.cta.shared::cta.inc.u32 %0, [%1], 15;" : "=r"(r) : "r"(a) : "memory");
  return r;
}
__device__ __forceinline__ void red_max_s(uint32_t a, uint32_t v) { asm volatile("red.shared::cta.max.u32 [%0], %1;" ::"r"(a), "r"(v) : "memory"); }
__device__ __forceinline__ uint32_t lds32(uint32_t a) { uint32_t r; asm volatile("ld.shared.u32 %0, [%1];" : "=r"(r) : "r"(a) : "memory"); return r; }
__device__ __forceinline__ float ldsf(uint32_t a) { return __uint_as_float(lds32(a)); }
__device__ __forceinline__ void sts32(uint32_t a, uint32_t v) { asm volatile("st.shared.u32 [%0], %1;" ::"r"(a), "r"(v) : "memory"); }
__device__ __forceinline__ uint4 lds128(uint32_t a) {
  uint4 r;
  asm volatile("ld.shared.v4.u32 {%0,%1,%2,%3}, [%4];" : "=r"(r.x), "=r"(r.y), "=r"(r.z), "=r"(r.w) : "r"(a) : "memory");
  return r;
}
__device__ __forceinline__ void sts128(uint32_t a, uint4 v) { asm volatile("st.shared.v4.u32 [%0], {%1,%2,%3,%4};" ::"r"(a), "r"(v.x), "r"(v.y), "r"(v.z), "r"(v.w) : "memory"); }
__device__ __forceinline__ uint32_t pack_bf16(float lo, float hi) { uint32_t r; asm("cvt.rn.bf16x2.f32 %0, %1, %2;" : "=r"(r) : "f"(hi), "f"(lo)); return r; }
__device__ __forceinline__ uint32_t pack_f16(float lo, float hi) { uint32_t r; asm("cvt.rn.f16x2.f32 %0, %1, %2;" : "=r"(r) : "f"(hi), "f"(lo)); return r; }
__device__ __forceinline__ float bf_lo(uint32_t v) { return __uint_as_float(v << 16); }
__device__ __forceinline__ float bf_hi(uint32_t v) { return __uint_as_float(v & 0xFFFF0000u); }
__device__ __forceinline__ float ex2(float a) { float x; asm("ex2.approx.ftz.f32 %0, %1;" : "=f"(x) : "f"(a)); return x; }
__device__ __forceinline__ void warp_signal(unsigned int* cnt) {
  fence_async();
  __syncwarp();
  if (elect()) asm volatile("red.release.gpu.global.add.u32 [%0], 1;" ::"l"(cnt) : "memory");
}
__device__ __forceinline__ void wait_count(const unsigned int* cnt, uint32_t target) {
#pragma unroll 1
  for (int i = 0; i < (1 << 21); i++) {
    uint32_t v;
    asm volatile("ld.acquire.gpu.global.u32 %0, [%1];" : "=r"(v) : "l"(cnt) : "memory");
    if ((int)(v - target) >= 0) { fence_async(); return; }
  }
  __trap();
}

#define R4(d, i) "+f"(d[i]), "+f"(d[i + 1]), "+f"(d[i + 2]), "+f"(d[i + 3])
#define R8(d, i) R4(d, i), R4(d, i + 4)
#define R32(d, i) R8(d, i), R8(d, i + 8), R8(d, i + 16), R8(d, i + 24)
#define L4 "%0,%1,%2,%3"
#define L8 L4 ",%4,%5,%6,%7"
#define L12 L8 ",%8,%9,%10,%11"
#define L32 L12 ",%12,%13,%14,%15,%16,%17,%18,%19,%20,%21,%22,%23,%24,%25,%26,%27,%28,%29,%30,%31"
#define L64 L32 ",%32,%33,%34,%35,%36,%37,%38,%39,%40,%41,%42,%43,%44,%45,%46,%47,%48,%49,%50,%51,%52,%53,%54,%55,%56,%57,%58,%59,%60,%61,%62,%63"
__device__ __forceinline__ void mma_ss128(float* d, uint64_t da, uint64_t db, int sd) {
  asm volatile("{\n.reg .pred p;\nsetp.ne.b32 p, %66, 0;\nwgmma.mma_async.sync.aligned.m64n128k16.f32.bf16.bf16 {" L64 "}, %64, %65, p, 1, 1, 0, 1;\n}\n"
               : R32(d, 0), R32(d, 32) : "l"(da), "l"(db), "r"(sd));
}
__device__ __forceinline__ void mma_ss16(float* d, uint64_t da, uint64_t db) {
  asm volatile("wgmma.mma_async.sync.aligned.m64n16k16.f32.bf16.bf16 {" L8 "}, %8, %9, 1, 1, 1, 0, 1;\n" : R8(d, 0) : "l"(da), "l"(db));
}
__device__ __forceinline__ void mma_ss8(float* d, uint64_t da, uint64_t db) {
  asm volatile("wgmma.mma_async.sync.aligned.m64n8k16.f32.bf16.bf16 {" L4 "}, %4, %5, 1, 1, 1, 0, 0;\n" : R4(d, 0) : "l"(da), "l"(db));
}
__device__ __forceinline__ void mma_qk_f16(float* d, const uint32_t* a, uint64_t db) {
  asm volatile("wgmma.mma_async.sync.aligned.m64n64k16.f32.f16.f16 {" L32 "}, {%32,%33,%34,%35}, %36, 1, 1, 1, 0;\n"
               : R32(d, 0) : "r"(a[0]), "r"(a[1]), "r"(a[2]), "r"(a[3]), "l"(db));
}
__device__ __forceinline__ void mma_qk_bf16(float* d, const uint32_t* a, uint64_t db) {
  asm volatile("wgmma.mma_async.sync.aligned.m64n64k16.f32.bf16.bf16 {" L32 "}, {%32,%33,%34,%35}, %36, 0, 1, 1, 0;\n"
               : R32(d, 0) : "r"(a[0]), "r"(a[1]), "r"(a[2]), "r"(a[3]), "l"(db));
}
__device__ __forceinline__ void mma_pv(float* d, const uint32_t* a, uint64_t db) {
  asm volatile("wgmma.mma_async.sync.aligned.m64n24k16.f32.bf16.bf16 {" L12 "}, {%12,%13,%14,%15}, %16, 1, 1, 1, 1;\n"
               : R8(d, 0), R4(d, 8) : "r"(a[0]), "r"(a[1]), "r"(a[2]), "r"(a[3]), "l"(db));
}

__device__ __forceinline__ uint32_t exp_mufu(float a, float b) { return pack_bf16(ex2(a), ex2(b)); }
constexpr float EXP_MAGIC = 446.0f + 0.00390625f - 0.5860f;
#define PM 0x5555u
constexpr uint32_t POLY_MASK = PM;
__device__ __forceinline__ uint32_t exp_soft(float t0, float t1, uint32_t cor) {
  uint32_t y = __byte_perm(__float_as_uint(t0), __float_as_uint(t1), 0x6521);
  uint32_t u, r;
  asm("lop3.b32 %0, %1, 0x007F007F, %2, 0xEA;" : "=r"(u) : "r"(y), "r"(cor));
  uint32_t e = y - u;
  asm("fma.rn.bf16x2 %0, %1, %2, %3;" : "=r"(r) : "r"(y), "r"(u), "r"(e));
  return r;
}
constexpr float QSCALE = 0.25f * 1.4426950408889634f;

template <bool FAST>
__device__ __forceinline__ void attn_pass(uint32_t sb, int pass, uint32_t& slot, uint32_t& ph, const unsigned char* kvsrc,
                                          uint32_t cor, unsigned char* odst) {
  const int tid = threadIdx.x, lane = tid & 31;
  uint32_t q[4], p[16];
  float o[12], s[32];
  float m0 = -INFINITY, m1 = -INFINITY;
  {
    uint4 v = lds128(sb + SM_Q + pass * 8192 + tid * 16);
    q[0] = v.x, q[1] = v.y, q[2] = v.z, q[3] = v.w;
    if (FAST) {
#pragma unroll
      for (int i = 0; i < 4; i++) q[i] = pack_f16(bf_lo(q[i]) * QSCALE, bf_hi(q[i]) * QSCALE);
    }
  }
#pragma unroll
  for (int i = 0; i < 12; i++) o[i] = 0.f;
#pragma unroll
  for (int j = 0; j < 32; j++) s[j] = (FAST && ((POLY_MASK >> (j / 2)) & 1)) ? EXP_MAGIC : 0.f;
  regfence<12>(o); regfence<32>(s); regfence<4>(q);
  uint32_t prev = 0;
  auto release = [&](uint32_t sl, int j) {
    if (j < 13 && elect()) {
      if (atom_inc_s(sb + SM_KCNT + sl * 4) == 15) {
        mbar_expect(sb + SM_KBAR + sl * 8, 16384);
        bulk_g2s(sb + SM_KV + sl * KVS, kvsrc + ((j + 3) & 7) * 16384, 16384, sb + SM_KBAR + sl * 8);
      }
    }
    __syncwarp();
  };
#pragma unroll 1
  for (int c = 0; c < 8; c++) {
    mbar_wait(sb + SM_KBAR + slot * 8, ph);
    const uint64_t dk = mkdesc(sb + SM_KV + slot * KVS, 128, 256, 0);
    const uint64_t dv = mkdesc(sb + SM_KV + slot * KVS + 8192, 128, 4096, 0);
#pragma unroll
    for (int h = 0; h < 4; h++) {
      wg_fence();
      if (FAST) mma_qk_f16(s, q, dk + h * 128); else mma_qk_bf16(s, q, dk + h * 128);
      wg_commit();
      wg_wait<0>();
      regfence<32>(s);
      if (h == 0 && c > 0) release(prev, pass * 8 + c - 1);
      if (FAST) {
#pragma unroll
        for (int j = 0; j < 16; j++)
          p[j] = ((POLY_MASK >> j) & 1) ? exp_soft(s[2 * j], s[2 * j + 1], cor) : exp_mufu(s[2 * j], s[2 * j + 1]);
      } else {
        regfence<12>(o);
        float n0 = m0, n1 = m1;
#pragma unroll
        for (int j = 0; j < 16; j++) {
          uint32_t r = pack_bf16(s[2 * j], s[2 * j + 1]);
          s[2 * j] = bf_lo(r), s[2 * j + 1] = bf_hi(r);
          if (j & 1) n1 = fmaxf(n1, fmaxf(s[2 * j], s[2 * j + 1])); else n0 = fmaxf(n0, fmaxf(s[2 * j], s[2 * j + 1]));
        }
        n0 = fmaxf(n0, __shfl_xor_sync(~0u, n0, 1)); n0 = fmaxf(n0, __shfl_xor_sync(~0u, n0, 2));
        n1 = fmaxf(n1, __shfl_xor_sync(~0u, n1, 1)); n1 = fmaxf(n1, __shfl_xor_sync(~0u, n1, 2));
        const float a0 = ex2((m0 - n0) * QSCALE), a1 = ex2((m1 - n1) * QSCALE);
        m0 = n0, m1 = n1;
#pragma unroll
        for (int i = 0; i < 12; i++) o[i] *= (i & 2) ? a1 : a0;
#pragma unroll
        for (int j = 0; j < 16; j++) {
          const float m = (j & 1) ? m1 : m0;
          p[j] = exp_mufu((s[2 * j] - m) * QSCALE, (s[2 * j + 1] - m) * QSCALE);
        }
        regfence<12>(o);
      }
      wg_fence();
#pragma unroll
      for (int i = 0; i < 4; i++) mma_pv(o, p + 4 * i, dv + (h * 4 + i) * 16);
      wg_commit();
    }
    prev = slot;
    if (++slot == 3) slot = 0, ph ^= 1;
  }
  wg_wait<0>();
  regfence<12>(o); regfence<32>(s);
  release(prev, pass * 8 + 7);
  const int row = ((tid >> 5) & 3) * 16 + (lane >> 2);
  const float l0 = __shfl_sync(~0u, o[8], lane & ~3), l1 = __shfl_sync(~0u, o[10], lane & ~3);
  const float r0 = __fdividef(ldsf(sb + SM_G + row * 4), l0), r1 = __fdividef(ldsf(sb + SM_G + row * 4 + 32), l1);
  uint32_t* op = (uint32_t*)odst;
  op[0] = pack_bf16(o[0] * r0, o[1] * r0);
  op[32] = pack_bf16(o[2] * r1, o[3] * r1);
  op[256] = pack_bf16(o[4] * r0, o[5] * r0);
  op[288] = pack_bf16(o[6] * r1, o[7] * r1);
}

struct Src { const CUtensorMap *m0, *m1; int x0, x1, y; uint32_t bytes; const unsigned char* a; };
__device__ __forceinline__ void issue_stage(uint32_t sb, int slot, const Src& s) {
  const uint32_t bar = sb + SM_BBAR + slot * 8, dst = sb + SM_B + slot * 16384;
  mbar_expect(bar, s.bytes);
  tma_load(dst, s.m0, s.x0, s.y, bar);
  tma_load(dst + 8192, s.m1, s.x1, s.y, bar);
  if (s.a) bulk_g2s(sb + SM_X + slot * 8192, s.a, 8192, bar);
}

__global__ void __launch_bounds__(640, 1)
fused_kernel(const __grid_constant__ Maps maps, const __nv_bfloat16* __restrict__ wk, const __nv_bfloat16* __restrict__ wv,
             const __nv_bfloat16* __restrict__ gw, const unsigned char* __restrict__ pf_gate, const unsigned char* __restrict__ pf_up,
             const unsigned char* __restrict__ pf_down, const unsigned char* __restrict__ pf_wo,
             const unsigned char* __restrict__ pf_x, const unsigned char* __restrict__ pf_wq, uint32_t cor) {
  extern __shared__ __align__(1024) unsigned char smem[];
  const uint32_t sb = (uint32_t)__cvta_generic_to_shared(smem);
  const int tid = threadIdx.x, wg = __shfl_sync(~0u, tid >> 7, 0), warp = (tid >> 5) & 3, lane = tid & 31;
  const int T = blockIdx.x >> 2, c = blockIdx.x & 3;
  if (tid == 512) {
    for (int i = 0; i < 8; i++) mbar_init(sb + SM_XBAR + 8 * i, 1);
    for (int i = 0; i < NB; i++) mbar_init(sb + SM_BBAR + 8 * i, 1), mbar_init(sb + SM_EBAR + 8 * i, 4);
    for (int i = 0; i < 3; i++) mbar_init(sb + SM_KBAR + 8 * i, 1);
    asm volatile("fence.mbarrier_init.release.cluster;" ::: "memory");
    TL(29);
    for (int i = 0; i < 8; i++) {
      mbar_expect(sb + SM_XBAR + 8 * i, 8192);
      tma_load(sb + SM_X + i * 8192, &maps.m[0], 64 * i, 64 * T, sb + SM_XBAR + 8 * i);
    }
    for (int i = 0; i < NB; i++) issue_stage(sb, i, Src{&maps.m[1], &maps.m[1], 128 * c, 128 * c + 64, 64 * i, 16384, nullptr});
    TL(30);
  } else if (tid == 608) {
    l2_prefetch(pf_x + blockIdx.x * 16384, 16384);
    l2_prefetch(pf_wq + blockIdx.x * 4096, 4096);
  } else if (tid >= 544 && tid < 552) {
    sts32(sb + SM_KCNT + (tid - 544) * 4, 0);
  } else if (tid >= 576 && tid < 581) {
    asm volatile("prefetch.tensormap [%0];" ::"l"(&maps.m[tid - 574]) : "memory");
  }
  const uint32_t epoch = g_epoch[blockIdx.x] + 1;
  if (wg == 0 && c < 2) {
    const uint4* src = (const uint4*)(c == 0 ? wk : wv);
    uint4 v[8];
#pragma unroll
    for (int i = 0; i < 8; i++) v[i] = __ldg(src + i * 128 + tid);
#pragma unroll
    for (int i = 0; i < 8; i++) sts128(sb + SM_KV + (tid & 1) * 8192 + (i * 64 + (tid >> 1)) * 16, v[i]);
    TL(31);
    fence_async_smem();
  } else if (wg == 1) {
    if (tid < 192) sts128(sb + SM_GW + (tid - 128) * 16, __ldg((const uint4*)gw + tid - 128));
    fence_async_smem();
  } else if (wg == 2 || wg == 3) {
#pragma unroll
    for (int i = 0; i < 3; i++) sts128(sb + SM_KV + i * KVS + 16384 + (tid - 256) * 16, make_uint4(0x3F80u, 0, 0, 0));
    fence_async_smem();
  }
  __syncthreads();
  if (wg == 3) { TL(26); }
  const uint64_t dx = mkdesc(sb + SM_X, 16, 1024, 1);

  if (wg < 4) {
    if (wg == 0 && c < 2) {
      float a[8];
#pragma unroll
      for (int i = 0; i < 8; i++) a[i] = 0.f;
      const uint64_t dw = mkdesc(sb + SM_KV, 128, 8192, 0);
      regfence<8>(a);
#pragma unroll 1
      for (int kb = 0; kb < 8; kb++) {
        mbar_wait(sb + SM_XBAR + kb * 8, 0);
        wg_fence();
#pragma unroll
        for (int k = 0; k < 4; k++) mma_ss16(a, dx + kb * 512 + k * 2, dw + (kb * 4 + k) * 16);
        wg_commit();
      }
      wg_wait<0>();
      regfence<8>(a);
      TL(0);
      const uint32_t st = sb + SM_KV + KVS;
      const uint32_t ad = st + (warp * 16 + (lane >> 2)) * 32 + (lane & 3) * 4;
      sts32(ad, pack_bf16(a[0], a[1]));
      sts32(ad + 256, pack_bf16(a[2], a[3]));
      sts32(ad + 16, pack_bf16(a[4], a[5]));
      sts32(ad + 272, pack_bf16(a[6], a[7]));
      bar_sync(5, 128);
      const int r = tid >> 1, hb = tid & 1, j = r >> 1, kk = (j & 3) * 64 + 2 * T + (r & 1);
      const uint4 v = lds128(st + tid * 16);
      if (c == 0) {
        uint4 w = make_uint4(0, 0, 0, 0);
        if (r >= 2) w = lds128(st + tid * 16 - 64);
        uint4 d;
        d.x = pack_f16(bf_lo(v.x) - bf_lo(w.x), bf_hi(v.x) - bf_hi(w.x));
        d.y = pack_f16(bf_lo(v.y) - bf_lo(w.y), bf_hi(v.y) - bf_hi(w.y));
        d.z = pack_f16(bf_lo(v.z) - bf_lo(w.z), bf_hi(v.z) - bf_hi(w.z));
        d.w = pack_f16(bf_lo(v.w) - bf_lo(w.w), bf_hi(v.w) - bf_hi(w.w));
        const int off = (j >> 2) * 16384 + (kk >> 3) * 256 + hb * 128 + (kk & 7) * 16;
        *(uint4*)(g_kv[0] + off) = d;
        *(uint4*)(g_kv[1] + off) = v;
      } else {
        const int off = (j >> 2) * 16384 + 8192 + hb * 4096 + kk * 16;
        *(uint4*)(g_kv[0] + off) = v;
        *(uint4*)(g_kv[1] + off) = v;
      }
      float n2 = bf_lo(v.x) * bf_lo(v.x) + bf_hi(v.x) * bf_hi(v.x) + bf_lo(v.y) * bf_lo(v.y) + bf_hi(v.y) * bf_hi(v.y) +
                 bf_lo(v.z) * bf_lo(v.z) + bf_hi(v.z) * bf_hi(v.z) + bf_lo(v.w) * bf_lo(v.w) + bf_hi(v.w) * bf_hi(v.w);
      n2 += __shfl_xor_sync(~0u, n2, 1);
      const uint32_t mx = __reduce_max_sync(~0u, __float_as_uint(n2) & 0x7FFFFFFFu);
      if (lane == 0) red_max_s(sb + SM_MAX + 12, mx);
      fence_async();
      bar_sync(5, 128);
      if (tid == 0) {
        const unsigned long long f = ((unsigned long long)epoch << 32) | lds32(sb + SM_MAX + 12);
        asm volatile("st.release.gpu.global.u64 [%0], %1;" ::"l"(g_kvflag + 2 * T + c), "l"(f) : "memory");
      }
      TL(1);
    } else if (wg == 1) {
      float a[4] = {0.f, 0.f, 0.f, 0.f};
      const uint64_t dw = mkdesc(sb + SM_GW, 16, 128, 0);
      regfence<4>(a);
#pragma unroll 1
      for (int kb = 0; kb < 8; kb++) {
        mbar_wait(sb + SM_XBAR + kb * 8, 0);
        wg_fence();
#pragma unroll
        for (int k = 0; k < 4; k++) mma_ss8(a, dx + kb * 512 + k * 2, dw + (kb * 4 + k) * 2);
        wg_commit();
      }
      if (tid == 128) {
        l2_prefetch(pf_gate + blockIdx.x * 14336, 14336);
        l2_prefetch(pf_up + blockIdx.x * 14336, 14336);
        l2_prefetch(pf_down + blockIdx.x * 14336, 14336);
        l2_prefetch(pf_wo + blockIdx.x * 4096, 4096);
      }
      __syncwarp();
      wg_wait<0>();
      regfence<4>(a);
      if ((lane & 3) == 0) {
        const uint32_t ad = sb + SM_G + (warp * 16 + (lane >> 2)) * 4;
        sts32(ad, __float_as_uint(1.f / (1.f + __expf(-a[0]))));
        sts32(ad + 32, __float_as_uint(1.f / (1.f + __expf(-a[2]))));
      }
      TL(2);
    }
    if (wg < 2) bar_arrive(3, 384);
    bar_sync(1, 640);
    {
      float n0 = 0.f, n1 = 0.f;
#pragma unroll
      for (int p = 0; p < 2; p++) {
        const uint4 v = lds128(sb + SM_Q + p * 8192 + tid * 16);
        float a = bf_lo(v.x) * bf_lo(v.x) + bf_hi(v.x) * bf_hi(v.x) + bf_lo(v.z) * bf_lo(v.z) + bf_hi(v.z) * bf_hi(v.z);
        float b = bf_lo(v.y) * bf_lo(v.y) + bf_hi(v.y) * bf_hi(v.y) + bf_lo(v.w) * bf_lo(v.w) + bf_hi(v.w) * bf_hi(v.w);
        a += __shfl_xor_sync(~0u, a, 1); a += __shfl_xor_sync(~0u, a, 2);
        b += __shfl_xor_sync(~0u, b, 1); b += __shfl_xor_sync(~0u, b, 2);
        if (p == 0) n0 = a, n1 = b;
        else n0 = __uint_as_float(max(__float_as_uint(n0) & 0x7FFFFFFFu, __float_as_uint(a) & 0x7FFFFFFFu)),
             n1 = __uint_as_float(max(__float_as_uint(n1) & 0x7FFFFFFFu, __float_as_uint(b) & 0x7FFFFFFFu));
      }
      const uint32_t mx = __reduce_max_sync(~0u, max(__float_as_uint(n0), __float_as_uint(n1)));
      if (lane == 0) red_max_s(sb + SM_MAX, mx);
    }
    if (tid >= 256 && tid < 288) {
      unsigned long long fk, fv;
      bool ok = false;
#pragma unroll 1
      for (int i = 0; i < (1 << 21) && !ok; i++) {
        asm volatile("ld.relaxed.gpu.global.v2.u64 {%0, %1}, [%2];" : "=l"(fk), "=l"(fv) : "l"(g_kvflag + 2 * lane) : "memory");
        ok = __all_sync(~0u, (uint32_t)(fk >> 32) == epoch && (uint32_t)(fv >> 32) == epoch);
      }
      if (!ok) __trap();
      fence_acquire();
      fence_async();
      __syncwarp();
      if (lane < 3) {
        mbar_expect(sb + SM_KBAR + lane * 8, 16384);
        bulk_g2s(sb + SM_KV + lane * KVS, g_kv[0] + lane * 16384, 16384, sb + SM_KBAR + lane * 8);
      }
      const uint32_t km = __reduce_max_sync(~0u, (uint32_t)fk), vm = __reduce_max_sync(~0u, (uint32_t)fv);
      if (lane == 0) sts32(sb + SM_MAX + 4, km), sts32(sb + SM_MAX + 8, vm);
      TL(3);
    }
    bar_sync(2, 512);
    const float qm = ldsf(sb + SM_MAX), km = ldsf(sb + SM_MAX + 4), vm = ldsf(sb + SM_MAX + 8);
    const bool fast = qm * km * (QSCALE * QSCALE) <= 48.f * 48.f && qm <= 1048576.f && km <= 1048576.f && vm <= 1e30f;
    unsigned char* odst = g_o + (T * 8 + 2 * c) * 8192 + wg * 2048 + warp * 256 + lane * 4;
    unsigned int* ocnt = g_cnt + (T * 3 + 1) * 32;
    uint32_t slot = 0, ph = 0;
    if (fast) {
#pragma unroll 1
      for (int pass = 0; pass < 2; pass++) {
        attn_pass<true>(sb, pass, slot, ph, g_kv[0], cor, odst + pass * 8192);
        warp_signal(ocnt + pass * 32);
        TL(4 + wg * 2 + pass);
      }
    } else {
      if (tid < 3) {
        mbar_wait(sb + SM_KBAR + tid * 8, 0);
        mbar_expect(sb + SM_KBAR + tid * 8, 16384);
        bulk_g2s(sb + SM_KV + tid * KVS, g_kv[1] + tid * 16384, 16384, sb + SM_KBAR + tid * 8);
      }
      bar_sync(2, 512);
      ph = 1;
#pragma unroll 1
      for (int pass = 0; pass < 2; pass++) {
        attn_pass<false>(sb, pass, slot, ph, g_kv[1], cor, odst + pass * 8192);
        warp_signal(ocnt + pass * 32);
      }
    }
  } else {
    float acc[64];
    const int wu = __shfl_sync(~0u, warp, 0);
    auto release = [&](int sl, uint32_t ph, bool refill, const Src& src) {
      if (elect()) mbar_arrive(sb + SM_EBAR + sl * 8);
      if (refill && wu == sl) {
        mbar_wait(sb + SM_EBAR + sl * 8, ph);
        if (elect()) issue_stage(sb, sl, src);
      }
    };
    auto stage = [&](int sl, uint32_t ph, uint64_t da, int ka, bool first) {
      mbar_wait(sb + SM_BBAR + sl * 8, ph);
      const uint64_t db = mkdesc(sb + SM_B + sl * 16384, 8192, 1024, 1);
      wg_fence();
      mma_ss128(acc, da, db, !first);
#pragma unroll
      for (int k = 1; k < 4; k++) mma_ss128(acc, da + k * ka, db + k * 128, 1);
      wg_commit();
    };
#pragma unroll 1
    for (int u = 0; u < 8; u++) {
      Src cur, nxt;
      if (u == 0) cur = Src{&maps.m[1], &maps.m[1], 128 * c, 128 * c + 64, 0, 16384, nullptr};
      else cur = Src{&maps.m[2], &maps.m[3], 448 * c + 64 * u - 64, 448 * c + 64 * u - 64, 0, 16384, nullptr};
      if (u == 7) nxt = Src{&maps.m[4], &maps.m[4], 128 * c, 128 * c + 64, 0, 24576, nullptr};
      else nxt = Src{&maps.m[2], &maps.m[3], 448 * c + 64 * u, 448 * c + 64 * u, 0, 16384, nullptr};
#pragma unroll
      for (int kb = 0; kb < 9; kb++) {
        if (kb < 8) {
          if (u == 0) mbar_wait(sb + SM_XBAR + kb * 8, 0);
          stage(kb & 3, kb >> 2, dx + kb * 512, 2, kb == 0);
        }
        if (kb > 0) {
          if (kb < 8) wg_wait<1>(); else wg_wait<0>();
          Src t = kb < 5 ? cur : nxt;
          t.y = ((kb + 3) & 7) * 64;
          release((kb - 1) & 3, (kb - 1) >> 2, true, t);
        }
      }
      regfence<64>(acc);
      if (u == 0) {
#pragma unroll
        for (int h = 0; h < 8; h++)
          sts128(sb + SM_Q + h * 2048 + (tid - 512) * 16,
                 make_uint4(pack_bf16(acc[8 * h], acc[8 * h + 1]), pack_bf16(acc[8 * h + 2], acc[8 * h + 3]),
                            pack_bf16(acc[8 * h + 4], acc[8 * h + 5]), pack_bf16(acc[8 * h + 6], acc[8 * h + 7])));
        bar_arrive(1, 640);
      } else {
        uint32_t* hp = (uint32_t*)(g_h + (T * 28 + c * 7 + u - 1) * 8192 + warp * 256) + lane;
#pragma unroll
        for (int j = 0; j < 16; j++) {
          float h[2];
#pragma unroll
          for (int e = 0; e < 2; e++) {
            const float x = acc[2 * j + e];
            float t;
            asm("tanh.approx.f32 %0, %1;" : "=f"(t) : "f"(x * fmaf(x * x, 0.044715f * 0.7978845608028654f, 0.7978845608028654f)));
            const float w = 0.5f * x * acc[32 + 2 * j + e];
            h[e] = fmaf(w, t, w);
          }
          hp[(j >> 1) * 256 + (j & 1) * 32] = pack_bf16(h[0], h[1]);
        }
      }
      TL(12 + u);
    }
    warp_signal(g_cnt + T * 96);
    bar_sync(3, 384);
    const unsigned char* hsrc = g_h + T * 28 * 8192;
    if (wu == 0 && elect()) {
      wait_count(g_cnt + T * 96, epoch * 16);
#pragma unroll
      for (int j = 0; j < NB; j++) bulk_g2s(sb + SM_X + j * 8192, hsrc + j * 8192, 8192, sb + SM_BBAR + j * 8);
    }
    __syncwarp();
    TL(20);
    const uint64_t da0 = mkdesc(sb + SM_X, 1024, 128, 0);
#pragma unroll 1
    for (int g = 0; g < 7; g++) {
#pragma unroll
      for (int j = 0; j < 4; j++) {
        stage(j, g & 1, da0 + j * 512, 128, g == 0 && j == 0);
        if (j > 0 || g > 0) {
          wg_wait<1>();
          const int n = 4 * g + j + 3;
          Src t{&maps.m[4], &maps.m[4], 128 * c, 128 * c + 64, n * 64, 24576, hsrc + n * 8192};
          if (j > 0 && g == 6) t.m0 = t.m1 = &maps.m[5], t.y = (j - 1) * 128, t.a = nullptr;
          release((j + 3) & 3, (j == 0 ? g + 1 : g) & 1, true, t);
        }
      }
    }
    wg_wait<0>();
    regfence<64>(acc);
    release(3, 0, true, Src{&maps.m[5], &maps.m[5], 128 * c, 128 * c + 64, 384, 24576, nullptr});
    TL(21);
    {
      const uint32_t ad = sb + SM_G + (warp * 16 + (lane >> 2)) * 4;
      const float s0 = 1.f - ldsf(ad), s1 = 1.f - ldsf(ad + 32);
#pragma unroll
      for (int j = 0; j < 64; j++) acc[j] *= (j & 2) ? s1 : s0;
      regfence<64>(acc);
    }
    bar_sync(4, 128);
#pragma unroll 1
    for (int p = 0; p < 2; p++) {
      if (wu == 0 && elect()) {
        wait_count(g_cnt + T * 96 + 32 + p * 32, epoch * 64);
#pragma unroll
        for (int j = 0; j < 4; j++)
          bulk_g2s(sb + SM_X + (p * 4 + j) * 8192, g_o + (T * 8 + 2 * j + p) * 8192, 8192, sb + SM_BBAR + j * 8);
      }
      __syncwarp();
      TL(22 + p);
#pragma unroll
      for (int j = 0; j < 5; j++) {
        if (j < 4) stage(j, p ^ 1, da0 + (p * 4 + j) * 512, 128, false);
        if (j > 0) {
          if (j < 4) wg_wait<1>(); else wg_wait<0>();
          release(j - 1, 1, p == 0, Src{&maps.m[5], &maps.m[5], 128 * c, 128 * c + 64, (j - 1) * 128 + 64, 24576, nullptr});
        }
      }
    }
    regfence<64>(acc);
    TL(24);
    {
      const int r = (lane & 7) + (lane & 8);
      const uint32_t wb = sb + SM_Q + warp * 4096;
#pragma unroll
      for (int j = 0; j < 8; j++) {
        const int blk = 2 * j + (lane >> 4);
        const uint32_t ad = wb + (blk >> 3) * 2048 + r * 128 + (((blk & 7) ^ (r & 7)) << 4);
        asm volatile("stmatrix.sync.aligned.m8n8.x4.shared.b16 [%0], {%1,%2,%3,%4};" ::"r"(ad),
                     "r"(pack_bf16(acc[8 * j], acc[8 * j + 1])), "r"(pack_bf16(acc[8 * j + 2], acc[8 * j + 3])),
                     "r"(pack_bf16(acc[8 * j + 4], acc[8 * j + 5])), "r"(pack_bf16(acc[8 * j + 6], acc[8 * j + 7])) : "memory");
      }
      fence_async_smem();
      __syncwarp();
      if (lane == 0) {
        tma_store(&maps.m[6], 128 * c, 64 * T + 16 * warp, wb);
        tma_store(&maps.m[6], 128 * c + 64, 64 * T + 16 * warp, wb + 2048);
        asm volatile("cp.async.bulk.commit_group;" ::: "memory");
        if (warp == 0) g_epoch[blockIdx.x] = epoch;
        asm volatile("cp.async.bulk.wait_group.read 0;" ::: "memory");
      }
    }
    TL(25);
  }
}

typedef CUresult (*EncodeFn)(CUtensorMap*, CUtensorMapDataType, cuuint32_t, void*, const cuuint64_t*, const cuuint64_t*,
                             const cuuint32_t*, const cuuint32_t*, CUtensorMapInterleave, CUtensorMapSwizzle,
                             CUtensorMapL2promotion, CUtensorMapFloatOOBfill);

void make_map(EncodeFn fn, CUtensorMap* m, void* p, int rows, int cols, int box_rows) {
  cuuint64_t dims[2] = {(cuuint64_t)cols, (cuuint64_t)rows};
  cuuint64_t strides[1] = {(cuuint64_t)cols * 2};
  cuuint32_t box[2] = {64, (cuuint32_t)box_rows};
  cuuint32_t es[2] = {1, 1};
  fn(m, CU_TENSOR_MAP_DATA_TYPE_BFLOAT16, 2, p, dims, strides, box, es, CU_TENSOR_MAP_INTERLEAVE_NONE,
     CU_TENSOR_MAP_SWIZZLE_128B, CU_TENSOR_MAP_L2_PROMOTION_L2_128B, CU_TENSOR_MAP_FLOAT_OOB_FILL_NONE);
}

}

extern "C" void kernel_launch(void* const* d_in, const int* in_sizes, int n_in, void* d_out, int out_size) {
  static EncodeFn fn = nullptr;
  if (!fn) {
    void* p = nullptr;
    cudaDriverEntryPointQueryResult st;
    cudaGetDriverEntryPoint("cuTensorMapEncodeTiled", &p, cudaEnableDefault, &st);
    fn = (EncodeFn)p;
    cudaFuncSetAttribute(fused_kernel, cudaFuncAttributeMaxDynamicSharedMemorySize, SM_TOTAL);
  }
  Maps maps;
  make_map(fn, &maps.m[0], d_in[0], 2048, 512, 64);
  make_map(fn, &maps.m[1], d_in[1], 512, 512, 64);
  make_map(fn, &maps.m[2], d_in[6], 512, 1792, 64);
  make_map(fn, &maps.m[3], d_in[7], 512, 1792, 64);
  make_map(fn, &maps.m[4], d_in[8], 1792, 512, 64);
  make_map(fn, &maps.m[5], d_in[4], 512, 512, 64);
  make_map(fn, &maps.m[6], d_out, 2048, 512, 16);
  fused_kernel<<<128, 640, SM_TOTAL>>>(maps, (const __nv_bfloat16*)d_in[2], (const __nv_bfloat16*)d_in[3],
                                       (const __nv_bfloat16*)d_in[9], (const unsigned char*)d_in[6], (const unsigned char*)d_in[7],
                                       (const unsigned char*)d_in[8], (const unsigned char*)d_in[4],
                                       (const unsigned char*)d_in[0], (const unsigned char*)d_in[1], 0x9F809F80u);
}
```

```cpp
#include <cuda_runtime.h>
#include <cuda_bf16.h>
#include <cuda_fp16.h>
#include <cuda.h>
#include <stdint.h>

namespace {

struct Scratch {
  unsigned char kv[2][131072];
  unsigned char h[32 * 28 * 8192];
  unsigned char o[128 * 8192];
  unsigned char ex[128 * 8192];
  unsigned long long kvflag[64];
  unsigned int flag[128 * 32];
  unsigned int epoch[128];
};
__device__ __align__(1024) Scratch g_scratch;
#define TL(i)
#define TLW(i)

struct Maps { CUtensorMap m[7]; };
struct Descs { uint64_t k, v, x, a, b; };

constexpr uint32_t KVB = 8192;
constexpr uint32_t KVS = 10240;
constexpr uint32_t SB = 1024;
constexpr uint32_t SM_X = SB;
constexpr uint32_t SM_B = SM_X + 65536;
constexpr uint32_t SM_KV = SM_B + 65536;
constexpr uint32_t SM_Q = SM_KV + 4 * KVS;
constexpr uint32_t SM_G = SM_Q + 16384;
constexpr uint32_t SM_XBAR = SM_G + 256;
constexpr uint32_t SM_BBAR = SM_XBAR + 32;
constexpr uint32_t SM_KBAR = SM_BBAR + 32;
constexpr uint32_t SM_EBAR = SM_KBAR + 32;
constexpr uint32_t SM_OBAR = SM_EBAR + 32;
constexpr uint32_t SM_FBAR = SM_OBAR + 32;
constexpr uint32_t SM_KEBAR = SM_FBAR + 8;
constexpr uint32_t SM_PBAR = SM_KEBAR + 32;
constexpr uint32_t SM_MAX = SM_PBAR + 8;
constexpr uint32_t SM_TOTAL = SM_MAX + 16 - SB;

__device__ __forceinline__ void wg_fence() { asm volatile("wgmma.fence.sync.aligned;" ::: "memory"); }
__device__ __forceinline__ void wg_commit() { asm volatile("wgmma.commit_group.sync.aligned;" ::: "memory"); }
template <int N> __device__ __forceinline__ void wg_wait() { asm volatile("wgmma.wait_group.sync.aligned %0;" ::"n"(N) : "memory"); }
template <int N> __device__ __forceinline__ void regfence(float* d) {
#pragma unroll
  for (int i = 0; i < N; i++) asm volatile("" : "+f"(d[i])::"memory");
}
template <int N> __device__ __forceinline__ void regfence(uint32_t* d) {
#pragma unroll
  for (int i = 0; i < N; i++) asm volatile("" : "+r"(d[i])::"memory");
}
__host__ __device__ constexpr uint64_t mkdesc(uint32_t addr, uint32_t lbo, uint32_t sbo, int sw) {
  return (uint64_t)((addr & 0x3FFFF) >> 4) | ((uint64_t)(lbo >> 4) << 16) | ((uint64_t)(sbo >> 4) << 32) | ((uint64_t)sw << 62);
}
__device__ __forceinline__ void mbar_init(uint32_t a, uint32_t c) { asm volatile("mbarrier.init.shared::cta.b64 [%0], %1;" ::"r"(a), "r"(c) : "memory"); }
__device__ __forceinline__ void mbar_expect(uint32_t a, uint32_t b) { asm volatile("mbarrier.arrive.expect_tx.shared::cta.b64 _, [%0], %1;" ::"r"(a), "r"(b) : "memory"); }
__device__ __forceinline__ bool mbar_try(uint32_t a, uint32_t ph) {
  uint32_t ok;
  asm volatile("{\n.reg .pred p;\nmbarrier.try_wait.parity.shared::cta.b64 p, [%1], %2;\nselp.u32 %0, 1, 0, p;\n}" : "=r"(ok) : "r"(a), "r"(ph) : "memory");
  return ok;
}
__device__ __forceinline__ void mbar_wait(uint32_t a, uint32_t ph) {
  if (mbar_try(a, ph)) return;
#pragma unroll 1
  for (int i = 0; i < (1 << 20); i++)
    if (mbar_try(a, ph)) return;
  __trap();
}
__device__ __forceinline__ void bulk_g2s(uint32_t dst, const void* src, uint32_t bytes, uint32_t mbar) {
  asm volatile("cp.async.bulk.shared::cluster.global.mbarrier::complete_tx::bytes [%0], [%1], %2, [%3];" ::"r"(dst), "l"(src), "r"(bytes), "r"(mbar) : "memory");
}
__device__ __forceinline__ void tma_load(uint32_t dst, const CUtensorMap* m, int x, int y, uint32_t mbar) {
  asm volatile("cp.async.bulk.tensor.2d.shared::cluster.global.mbarrier::complete_tx::bytes [%0], [%1, {%2, %3}], [%4];" ::"r"(dst), "l"(m), "r"(x), "r"(y), "r"(mbar) : "memory");
}
__device__ __forceinline__ void tma_load3(uint32_t dst, const CUtensorMap* m, int y, int z, uint32_t mbar) {
  asm volatile("cp.async.bulk.tensor.3d.shared::cluster.global.mbarrier::complete_tx::bytes [%0], [%1, {0, %2, %3}], [%4];" ::"r"(dst), "l"(m), "r"(y), "r"(z), "r"(mbar) : "memory");
}
__device__ __forceinline__ void tma_store3(const CUtensorMap* m, int y, int z, uint32_t src) {
  asm volatile("cp.async.bulk.tensor.3d.global.shared::cta.bulk_group [%0, {0, %1, %2}], [%3];" ::"l"(m), "r"(y), "r"(z), "r"(src) : "memory");
}
__device__ __forceinline__ void tma_prefetch(const CUtensorMap* m, int x, int y) {
  asm volatile("cp.async.bulk.prefetch.tensor.2d.L2.global.tile [%0, {%1, %2}];" ::"l"(m), "r"(x), "r"(y) : "memory");
}
__device__ __forceinline__ void l2_prefetch(const void* p, uint32_t bytes) {
  asm volatile("cp.async.bulk.prefetch.L2.global [%0], %1;" ::"l"(p), "r"(bytes) : "memory");
}
__device__ __forceinline__ void fence_async() { asm volatile("fence.proxy.async.global;" ::: "memory"); }
__device__ __forceinline__ void fence_async_smem() { asm volatile("fence.proxy.async.shared::cta;" ::: "memory"); }
__device__ __forceinline__ void fence_acquire() { asm volatile("fence.acquire.gpu;" ::: "memory"); }
__device__ __forceinline__ bool elect() {
  uint32_t r;
  asm volatile("{\n.reg .pred p;\nelect.sync _|p, 0xffffffff;\nselp.u32 %0, 1, 0, p;\n}" : "=r"(r));
  return r;
}
__device__ __forceinline__ void mbar_arrive(uint32_t a) { asm volatile("mbarrier.arrive.shared::cta.b64 _, [%0];" ::"r"(a) : "memory"); }
__device__ __forceinline__ void bar_sync(int id, int n) { asm volatile("bar.sync %0, %1;" ::"r"(id), "r"(n) : "memory"); }
__device__ __forceinline__ void bar_arrive(int id, int n) { asm volatile("bar.arrive %0, %1;" ::"r"(id), "r"(n) : "memory"); }
__device__ __forceinline__ void red_max_s(uint32_t a, uint32_t v) { asm volatile("red.shared::cta.max.u32 [%0], %1;" ::"r"(a), "r"(v) : "memory"); }
__device__ __forceinline__ uint32_t lds32(uint32_t a) { uint32_t r; asm volatile("ld.shared.u32 %0, [%1];" : "=r"(r) : "r"(a) : "memory"); return r; }
__device__ __forceinline__ float ldsf(uint32_t a) { return __uint_as_float(lds32(a)); }
__device__ __forceinline__ void sts32(uint32_t a, uint32_t v) { asm volatile("st.shared.u32 [%0], %1;" ::"r"(a), "r"(v) : "memory"); }
__device__ __forceinline__ uint4 lds128(uint32_t a) {
  uint4 r;
  asm volatile("ld.shared.v4.u32 {%0,%1,%2,%3}, [%4];" : "=r"(r.x), "=r"(r.y), "=r"(r.z), "=r"(r.w) : "r"(a) : "memory");
  return r;
}
__device__ __forceinline__ void sts128(uint32_t a, uint4 v) { asm volatile("st.shared.v4.u32 [%0], {%1,%2,%3,%4};" ::"r"(a), "r"(v.x), "r"(v.y), "r"(v.z), "r"(v.w) : "memory"); }
__device__ __forceinline__ uint32_t pack_bf16(float lo, float hi) { uint32_t r; asm("cvt.rn.bf16x2.f32 %0, %1, %2;" : "=r"(r) : "f"(hi), "f"(lo)); return r; }
__device__ __forceinline__ uint32_t pack_f16(float lo, float hi) { uint32_t r; asm("cvt.rn.f16x2.f32 %0, %1, %2;" : "=r"(r) : "f"(hi), "f"(lo)); return r; }
__device__ __forceinline__ float bf_lo(uint32_t v) { return __uint_as_float(v << 16); }
__device__ __forceinline__ float bf_hi(uint32_t v) { return __uint_as_float(v & 0xFFFF0000u); }
__device__ __forceinline__ float ex2(float a) { float x; asm("ex2.approx.ftz.f32 %0, %1;" : "=f"(x) : "f"(a)); return x; }
__device__ __forceinline__ uint32_t ld_relaxed(const unsigned int* p) {
  uint32_t v;
  asm volatile("ld.relaxed.gpu.global.u32 %0, [%1];" : "=r"(v) : "l"(p) : "memory");
  return v;
}
__device__ __forceinline__ void wait_flag(const unsigned int* p, uint32_t v, uint32_t target) {
#pragma unroll 1
  for (int i = 0; i < (1 << 21) && (int)(v - target) < 0; i++) v = ld_relaxed(p);
  if ((int)(v - target) < 0) __trap();
  fence_acquire();
  fence_async();
}
__device__ __forceinline__ void stsm4(uint32_t a, uint32_t r0, uint32_t r1, uint32_t r2, uint32_t r3) {
  asm volatile("stmatrix.sync.aligned.m8n8.x4.shared.b16 [%0], {%1,%2,%3,%4};" ::"r"(a), "r"(r0), "r"(r1), "r"(r2), "r"(r3) : "memory");
}

#define R4(d, i) "+f"(d[i]), "+f"(d[i + 1]), "+f"(d[i + 2]), "+f"(d[i + 3])
#define R8(d, i) R4(d, i), R4(d, i + 4)
#define R32(d, i) R8(d, i), R8(d, i + 8), R8(d, i + 16), R8(d, i + 24)
#define L4 "%0,%1,%2,%3"
#define L8 L4 ",%4,%5,%6,%7"
#define L12 L8 ",%8,%9,%10,%11"
#define L32 L12 ",%12,%13,%14,%15,%16,%17,%18,%19,%20,%21,%22,%23,%24,%25,%26,%27,%28,%29,%30,%31"
#define L64 L32 ",%32,%33,%34,%35,%36,%37,%38,%39,%40,%41,%42,%43,%44,%45,%46,%47,%48,%49,%50,%51,%52,%53,%54,%55,%56,%57,%58,%59,%60,%61,%62,%63"
__device__ __forceinline__ void mma_ss128(float* d, uint64_t da, uint64_t db, int sd) {
  asm volatile("{\n.reg .pred p;\nsetp.ne.b32 p, %66, 0;\nwgmma.mma_async.sync.aligned.m64n128k16.f32.bf16.bf16 {" L64 "}, %64, %65, p, 1, 1, 0, 1;\n}\n"
               : R32(d, 0), R32(d, 32) : "l"(da), "l"(db), "r"(sd));
}
__device__ __forceinline__ void mma_ss24(float* d, uint64_t da, uint64_t db) {
  asm volatile("wgmma.mma_async.sync.aligned.m64n24k16.f32.bf16.bf16 {" L12 "}, %12, %13, 1, 1, 1, 0, 1;\n" : R8(d, 0), R4(d, 8) : "l"(da), "l"(db));
}
__device__ __forceinline__ void mma_qk_f16(float* d, const uint32_t* a, uint64_t db) {
  asm volatile("wgmma.mma_async.sync.aligned.m64n64k16.f32.f16.f16 {" L32 "}, {%32,%33,%34,%35}, %36, 1, 1, 1, 0;\n"
               : R32(d, 0) : "r"(a[0]), "r"(a[1]), "r"(a[2]), "r"(a[3]), "l"(db));
}
__device__ __forceinline__ void mma_qk_bf16(float* d, const uint32_t* a, uint64_t db) {
  asm volatile("wgmma.mma_async.sync.aligned.m64n64k16.f32.bf16.bf16 {" L32 "}, {%32,%33,%34,%35}, %36, 0, 1, 1, 0;\n"
               : R32(d, 0) : "r"(a[0]), "r"(a[1]), "r"(a[2]), "r"(a[3]), "l"(db));
}
__device__ __forceinline__ void mma_pv(float* d, const uint32_t* a, uint64_t db) {
  asm volatile("wgmma.mma_async.sync.aligned.m64n24k16.f32.bf16.bf16 {" L12 "}, {%12,%13,%14,%15}, %16, 1, 1, 1, 1;\n"
               : R8(d, 0), R4(d, 8) : "r"(a[0]), "r"(a[1]), "r"(a[2]), "r"(a[3]), "l"(db));
}

__device__ __forceinline__ uint32_t exp_mufu(float a, float b) { return pack_bf16(ex2(a), ex2(b)); }
constexpr float EXP_MAGIC = 446.0f + 0.00390625f - 0.5860f;
#define PM 0x5555u
constexpr uint32_t POLY_MASK = PM;
__device__ __forceinline__ uint32_t exp_soft(float t0, float t1, uint32_t cor) {
  uint32_t y = __byte_perm(__float_as_uint(t0), __float_as_uint(t1), 0x6521);
  uint32_t u, r;
  asm("lop3.b32 %0, %1, 0x007F007F, %2, 0xEA;" : "=r"(u) : "r"(y), "r"(cor));
  uint32_t e = y - u;
  asm("fma.rn.bf16x2 %0, %1, %2, %3;" : "=r"(r) : "r"(y), "r"(u), "r"(e));
  return r;
}
constexpr float QSCALE = 0.25f * 1.4426950408889634f;

__host__ __device__ constexpr uint32_t off_k(int h) { return ((h >> 1) * KVS + (h & 1) * 2048) >> 4; }
__host__ __device__ constexpr uint32_t off_v(int h) { return ((h >> 1) * KVS + (h & 1) * 1024) >> 4; }

__device__ __forceinline__ void kv_advance(int sl, int it, int duty, const unsigned char* src) {
  if ((threadIdx.x & 31) == 0) mbar_arrive(SM_KEBAR + ((sl + 3) & 3) * 8);
  if (duty == sl) {
    const int t = (sl + 2) & 3;
    mbar_wait(SM_KEBAR + t * 8, (sl == 0 ? it + 1 : it) & 1);
    if (elect()) {
      mbar_expect(SM_KBAR + t * 8, KVB);
      bulk_g2s(SM_KV + t * KVS, src + ((4 * it + sl + 2) & 15) * KVB, KVB, SM_KBAR + t * 8);
    }
  }
}

__device__ __forceinline__ void attn_fast(int pass, int duty, const unsigned char* src, uint32_t cor, const Descs& d, float* o) {
  uint32_t q[4], p[16];
  float s[32];
  {
    const uint4 v = lds128(SM_Q + pass * 8192 + threadIdx.x * 16);
    q[0] = v.x, q[1] = v.y, q[2] = v.z, q[3] = v.w;
#pragma unroll
    for (int i = 0; i < 4; i++) q[i] = pack_f16(bf_lo(q[i]) * QSCALE, bf_hi(q[i]) * QSCALE);
  }
#pragma unroll
  for (int i = 0; i < 12; i++) o[i] = 0.f;
#pragma unroll
  for (int j = 0; j < 32; j++) s[j] = ((POLY_MASK >> (j / 2)) & 1) ? EXP_MAGIC : 0.f;
  regfence<12>(o); regfence<32>(s); regfence<4>(q);
#pragma unroll 1
  for (int it = 0; it < 4; it++) {
    if (pass + it == 4 && duty >= 2) duty = -1;
    mbar_wait(SM_KBAR, it & 1);
    wg_fence();
    mma_qk_f16(s, q, d.k);
    wg_commit();
#pragma unroll
    for (int h = 0; h < 8; h++) {
      wg_wait<0>();
      regfence<32>(s);
      if ((h & 1) == 0) kv_advance(h >> 1, it, duty, src);
#pragma unroll
      for (int j = 0; j < 16; j++)
        p[j] = ((POLY_MASK >> j) & 1) ? exp_soft(s[2 * j], s[2 * j + 1], cor) : exp_mufu(s[2 * j], s[2 * j + 1]);
      if (h < 7 && (h & 1)) mbar_wait(SM_KBAR + ((h + 1) >> 1) * 8, it & 1);
      wg_fence();
#pragma unroll
      for (int i = 0; i < 4; i++) mma_pv(o, p + 4 * i, d.v + off_v(h) + i * 16);
      if (h < 7) mma_qk_f16(s, q, d.k + off_k(h + 1));
      wg_commit();
    }
  }
  wg_wait<0>();
  regfence<12>(o); regfence<32>(s);
}

__device__ __forceinline__ void attn_safe(int pass, int duty, const unsigned char* src, const Descs& d, float* o) {
  uint32_t q[4], p[16];
  float s[32];
  float m0 = -INFINITY, m1 = -INFINITY;
  {
    const uint4 v = lds128(SM_Q + pass * 8192 + threadIdx.x * 16);
    q[0] = v.x, q[1] = v.y, q[2] = v.z, q[3] = v.w;
  }
#pragma unroll
  for (int i = 0; i < 12; i++) o[i] = 0.f;
#pragma unroll
  for (int j = 0; j < 32; j++) s[j] = 0.f;
  regfence<12>(o); regfence<32>(s); regfence<4>(q);
#pragma unroll 1
  for (int i = 0; i < 32; i++) {
    const int h = i & 7, it = i >> 3;
    if (pass + it == 4 && duty >= 2) duty = -1;
    mbar_wait(SM_KBAR + (h >> 1) * 8, it & 1);
    wg_fence();
    mma_qk_bf16(s, q, d.k + off_k(h));
    wg_commit();
    wg_wait<0>();
    regfence<32>(s); regfence<12>(o);
    if ((h & 1) == 0) kv_advance(h >> 1, it, duty, src);
    float n0 = m0, n1 = m1;
#pragma unroll
    for (int j = 0; j < 16; j++) {
      const uint32_t r = pack_bf16(s[2 * j], s[2 * j + 1]);
      s[2 * j] = bf_lo(r), s[2 * j + 1] = bf_hi(r);
      if (j & 1) n1 = fmaxf(n1, fmaxf(s[2 * j], s[2 * j + 1])); else n0 = fmaxf(n0, fmaxf(s[2 * j], s[2 * j + 1]));
    }
    n0 = fmaxf(n0, __shfl_xor_sync(~0u, n0, 1)); n0 = fmaxf(n0, __shfl_xor_sync(~0u, n0, 2));
    n1 = fmaxf(n1, __shfl_xor_sync(~0u, n1, 1)); n1 = fmaxf(n1, __shfl_xor_sync(~0u, n1, 2));
    const float a0 = ex2((m0 - n0) * QSCALE), a1 = ex2((m1 - n1) * QSCALE);
    m0 = n0, m1 = n1;
#pragma unroll
    for (int j = 0; j < 12; j++) o[j] *= (j & 2) ? a1 : a0;
#pragma unroll
    for (int j = 0; j < 16; j++) {
      const float m = (j & 1) ? m1 : m0;
      p[j] = exp_mufu((s[2 * j] - m) * QSCALE, (s[2 * j + 1] - m) * QSCALE);
    }
    regfence<12>(o);
    wg_fence();
#pragma unroll
    for (int j = 0; j < 4; j++) mma_pv(o, p + 4 * j, d.v + off_v(h) + j * 16);
    wg_commit();
  }
  wg_wait<0>();
  regfence<12>(o); regfence<32>(s);
}

__global__ void __launch_bounds__(640, 1)
fused_kernel(Scratch* __restrict__ sc, const __nv_bfloat16* __restrict__ wk, const __nv_bfloat16* __restrict__ wv,
             const unsigned short* __restrict__ gw, const unsigned char* __restrict__ pf_x, const unsigned char* __restrict__ pf_wq,
             const unsigned char* __restrict__ pf_down, const unsigned char* __restrict__ pf_wo, uint32_t cor,
             const __grid_constant__ Descs d, const __grid_constant__ Maps maps) {
  extern __shared__ __align__(1024) unsigned char smem[];
  const int tid = threadIdx.x, wg = __shfl_sync(~0u, tid >> 7, 0), warp = __shfl_sync(~0u, (tid >> 5) & 3, 0), lane = tid & 31;
  const int T = blockIdx.x >> 2, c = blockIdx.x & 3;

  if (wg == 4) {
    if (warp == 0) {
      if (lane < 26) mbar_init(SM_XBAR + lane * 8, lane < 12 ? 1 : lane < 21 ? 4 : 16);
      else if (lane < 28) sts32(SM_MAX + (lane - 26) * 4, 0);
      asm volatile("fence.mbarrier_init.release.cluster;" ::: "memory");
      __syncwarp();
      if (elect()) {
#pragma unroll
        for (int i = 0; i < 4; i++) {
          mbar_expect(SM_XBAR + 8 * i, 16384);
          tma_load3(SM_X + i * 16384, &maps.m[0], 64 * T, 2 * i, SM_XBAR + 8 * i);
        }
#pragma unroll
        for (int i = 0; i < 4; i++) {
          mbar_expect(SM_BBAR + 8 * i, 16384);
          tma_load3(SM_B + i * 16384, &maps.m[1], 64 * i, 2 * c, SM_BBAR + 8 * i);
        }
      }
      __syncwarp();
      TLW(29);
    } else if (warp == 3) {
      if (elect()) {
        l2_prefetch(pf_x + blockIdx.x * 16384, 16384);
        l2_prefetch(pf_wq + blockIdx.x * 4096, 4096);
      }
      if ((uint32_t)__cvta_generic_to_shared(smem) != SB) __trap();
    } else if (warp == 1) {
      if (lane < 5) asm volatile("prefetch.tensormap [%0];" ::"l"(&maps.m[lane + 2]) : "memory");
    }
    const uint32_t epoch = sc->epoch[blockIdx.x] + 1;
    bar_sync(0, 640);
    float acc[64];
    auto stage = [&](int sl, uint32_t ph, uint64_t da, int ka, bool first) {
      mbar_wait(SM_BBAR + sl * 8, ph);
      wg_fence();
      mma_ss128(acc, da, d.b + sl * 1024, !first);
#pragma unroll
      for (int k = 1; k < 4; k++) mma_ss128(acc, da + k * ka, d.b + sl * 1024 + k * 128, 1);
      wg_commit();
    };
    auto release = [&](int sl, uint32_t ph) {
      if (lane == 0) mbar_arrive(SM_EBAR + sl * 8);
      if (warp != sl) return false;
      mbar_wait(SM_EBAR + sl * 8, ph);
      return true;
    };
    const uint32_t bbar = SM_BBAR + warp * 8, bdst = SM_B + warp * 16384;
    auto load_w = [&](int m, int y) {
      if (elect()) {
        mbar_expect(bbar, 16384);
        tma_load3(bdst, &maps.m[m], y, 2 * c, bbar);
      }
    };
    auto load_gu = [&](int x, int y) {
      if (elect()) {
        mbar_expect(bbar, 16384);
        tma_load(bdst, &maps.m[2], x, y, bbar);
        tma_load(bdst + 8192, &maps.m[3], x, y, bbar);
      }
    };
    auto load_aw = [&](const unsigned char* a, int m, int y) {
      if (elect()) {
        mbar_expect(bbar, 24576);
        bulk_g2s(SM_X + warp * 8192, a, 8192, bbar);
        tma_load3(bdst, &maps.m[m], y, 2 * c, bbar);
      }
    };
    auto signal = [&](uint32_t v) {
      if (elect()) asm volatile("st.release.gpu.global.u32 [%0], %1;" ::"l"(sc->flag + blockIdx.x * 32), "r"(v) : "memory");
    };
    const unsigned int* pflag = sc->flag + (T * 4 + warp) * 32;
    const unsigned char* hsrc = sc->h + (T * 4 + warp) * 7 * 8192;
    uint32_t fv = 0;
    if (c < 2) bar_sync(7, 256);
#pragma unroll
    for (int kb = 0; kb < 9; kb++) {
      if (kb < 8) {
        if ((kb & 1) == 0) mbar_wait(SM_XBAR + kb * 4, 0);
        stage(kb & 3, kb >> 2, d.x + kb * 512, 2, kb == 0);
      }
      if (kb > 0) {
        if (kb < 8) wg_wait<1>(); else wg_wait<0>();
        if (release((kb - 1) & 3, (kb - 1) >> 2)) {
          if (kb < 5) load_w(1, (kb + 3) * 64); else load_gu(448 * c, (kb - 5) * 64);
        }
      }
    }
    regfence<64>(acc);
#pragma unroll
    for (int h = 0; h < 8; h++)
      sts128(SM_Q + h * 2048 + (tid - 512) * 16,
             make_uint4(pack_bf16(acc[8 * h], acc[8 * h + 1]), pack_bf16(acc[8 * h + 2], acc[8 * h + 3]),
                        pack_bf16(acc[8 * h + 4], acc[8 * h + 5]), pack_bf16(acc[8 * h + 6], acc[8 * h + 7])));
    bar_arrive(1, 640);
    TL(12);
#pragma unroll 1
    for (int u = 0; u < 7; u++) {
      const int x = 448 * c + 64 * u;
#pragma unroll
      for (int kb = 0; kb < 9; kb++) {
        if (kb < 8) stage(kb & 3, kb >> 2, d.x + kb * 512, 2, kb == 0);
        if (kb > 0) {
          if (kb < 8) wg_wait<1>(); else wg_wait<0>();
          if (release((kb - 1) & 3, (kb - 1) >> 2)) {
            if (kb < 5) {
              load_gu(x, (kb + 3) * 64);
              if (kb == 1 && u == 5) signal(2 * epoch - 1);
              if (u == 6) fv = ld_relaxed(pflag);
            } else if (u < 6) {
              load_gu(x + 64, (kb - 5) * 64);
            } else {
              wait_flag(pflag, fv, 2 * epoch - 1);
              load_aw(hsrc, 4, warp * 448);
            }
          }
        }
      }
      regfence<64>(acc);
      uint32_t* hp = (uint32_t*)(sc->h + (blockIdx.x * 7 + u) * 8192 + warp * 256) + lane;
#pragma unroll
      for (int j = 0; j < 16; j++) {
        float h[2];
#pragma unroll
        for (int e = 0; e < 2; e++) {
          const float x = acc[2 * j + e];
          float t;
          asm("tanh.approx.f32 %0, %1;" : "=f"(t) : "f"(x * fmaf(x * x, 0.044715f * 0.7978845608028654f, 0.7978845608028654f)));
          const float w = x * acc[32 + 2 * j + e];
          h[e] = fmaf(w, t, w);
        }
        hp[(j >> 1) * 256 + (j & 1) * 32] = pack_bf16(h[0], h[1]);
      }
      __syncwarp();
      TL(13 + u);
    }
    if (lane == 0) mbar_arrive(SM_FBAR);
    const unsigned char* osrc = sc->o + (T * 4 + warp) * 8192;
#pragma unroll 1
    for (int g = 0; g < 7; g++) {
#pragma unroll
      for (int j = 0; j < 4; j++) {
        stage(j, g & 1, d.a + j * 512, 128, g == 0 && j == 0);
        wg_wait<1>();
        const int n = j == 0 ? g : g + 1;
        if ((j > 0 || g > 0) && release((j + 3) & 3, (n + 1) & 1)) {
          if (n == 5) wait_flag(pflag, fv, 2 * epoch);
          if (n < 7) load_aw(hsrc + n * 8192, 4, warp * 448 + n * 64); else load_aw(osrc, 5, warp * 128);
          if (n == 4) fv = ld_relaxed(pflag);
          if (j == 1 && n == 2) {
            mbar_wait(SM_PBAR, 0);
            signal(2 * epoch);
          }
        }
      }
    }
    wg_wait<0>();
    if (release(3, 0)) load_aw(osrc, 5, warp * 128);
    regfence<64>(acc);
    TL(20);
    {
      const uint32_t ad = SM_G + (warp * 16 + (lane >> 2)) * 4;
      const float s0 = 0.5f - 0.5f * ldsf(ad), s1 = 0.5f - 0.5f * ldsf(ad + 32);
#pragma unroll
      for (int j = 0; j < 64; j++) acc[j] *= (j & 2) ? s1 : s0;
      regfence<64>(acc);
    }
#pragma unroll
    for (int j = 0; j < 5; j++) {
      if (j < 4) stage(j, 1, d.a + j * 512, 128, false);
      if (j > 0) {
        if (j < 4) wg_wait<1>(); else wg_wait<0>();
        if (release(j - 1, 1)) load_w(5, warp * 128 + 64);
      }
    }
    TL(21);
#pragma unroll
    for (int j = 0; j < 4; j++) mbar_wait(SM_BBAR + j * 8, 0);
    if (tid == 512) sc->epoch[blockIdx.x] = epoch;
    TL(22);
#pragma unroll
    for (int w = 0; w < 4; w++) {
      mbar_wait(SM_OBAR + w * 8, 0);
      wg_fence();
#pragma unroll
      for (int j = 0; j < 4; j++) mma_ss128(acc, d.a + (4 + j) * 512 + w * 128, d.b + j * 1024 + w * 128, 1);
      wg_commit();
    }
    TL(23);
    wg_wait<0>();
    regfence<64>(acc);
    TL(24);
    {
      const int r = (lane & 7) + (lane & 8);
      const uint32_t wb = SM_Q + warp * 4096;
#pragma unroll
      for (int j = 0; j < 8; j++) {
        const int blk = 2 * j + (lane >> 4);
        stsm4(wb + (blk >> 3) * 2048 + r * 128 + (((blk & 7) ^ (r & 7)) << 4),
              pack_bf16(acc[8 * j], acc[8 * j + 1]), pack_bf16(acc[8 * j + 2], acc[8 * j + 3]),
              pack_bf16(acc[8 * j + 4], acc[8 * j + 5]), pack_bf16(acc[8 * j + 6], acc[8 * j + 7]));
      }
      fence_async_smem();
      __syncwarp();
      if (elect()) {
        tma_store3(&maps.m[6], 64 * T + 16 * warp, 2 * c, wb);
        asm volatile("cp.async.bulk.commit_group;" ::: "memory");
        asm volatile("cp.async.bulk.wait_group.read 0;" ::: "memory");
      }
    }
    TL(25);
  } else {
    uint32_t epoch = 0;
    if (wg == 0) {
      uint4 v[8];
      if (c < 2) {
        const uint4* src = (const uint4*)(c == 0 ? wk : wv);
#pragma unroll
        for (int i = 0; i < 8; i++) v[i] = __ldg(src + i * 128 + tid);
        epoch = sc->epoch[blockIdx.x] + 1;
      }
      bar_sync(0, 640);
      if (c < 2) {
#pragma unroll
        for (int i = 0; i < 8; i++) sts128(SM_KV + KVS + (tid & 1) * KVS + (i * 64 + (tid >> 1)) * 16, v[i]);
        fence_async_smem();
      }
      bar_sync(5, 256);
      TL(31);
      float a[12];
#pragma unroll
      for (int i = 0; i < 12; i++) a[i] = 0.f;
      constexpr uint64_t dw = mkdesc(SM_KV + KVS, 128, KVS, 0);
      regfence<12>(a);
#pragma unroll
      for (int kb = 0; kb < 4; kb++) {
        mbar_wait(SM_XBAR + kb * 8, 0);
        if (kb == 0) { TL(27); }
        if (kb == 3) { TL(28); }
        wg_fence();
#pragma unroll
        for (int k = 0; k < 8; k++) mma_ss24(a, d.x + kb * 1024 + (k >> 2) * 512 + (k & 3) * 2, dw + (kb * 8 + k) * 16);
        wg_commit();
      }
      wg_wait<0>();
      regfence<12>(a);
      TL(0);
      if (c < 2) {
        bar_arrive(7, 256);
        const uint32_t ad = SM_KV + (warp * 16 + (lane >> 2)) * 32 + (lane & 3) * 4;
        sts32(ad, pack_bf16(a[0], a[1]));
        sts32(ad + 256, pack_bf16(a[2], a[3]));
        sts32(ad + 16, pack_bf16(a[4], a[5]));
        sts32(ad + 272, pack_bf16(a[6], a[7]));
        bar_sync(6, 128);
        const int r = tid >> 1, hb = tid & 1, j = r >> 1, kk = (j & 1) * 64 + 2 * T + (r & 1);
        const uint4 v = lds128(SM_KV + tid * 16);
        if (c == 0) {
          uint4 w = make_uint4(0, 0, 0, 0);
          if (r >= 2) w = lds128(SM_KV + tid * 16 - 64);
          uint4 e;
          e.x = pack_f16(bf_lo(v.x) - bf_lo(w.x), bf_hi(v.x) - bf_hi(w.x));
          e.y = pack_f16(bf_lo(v.y) - bf_lo(w.y), bf_hi(v.y) - bf_hi(w.y));
          e.z = pack_f16(bf_lo(v.z) - bf_lo(w.z), bf_hi(v.z) - bf_hi(w.z));
          e.w = pack_f16(bf_lo(v.w) - bf_lo(w.w), bf_hi(v.w) - bf_hi(w.w));
          const int off = (j >> 1) * KVB + (kk >> 3) * 256 + hb * 128 + (kk & 7) * 16;
          *(uint4*)(sc->kv[0] + off) = e;
          *(uint4*)(sc->kv[1] + off) = v;
        } else {
          const int off = (j >> 1) * KVB + 4096 + hb * 2048 + kk * 16;
          *(uint4*)(sc->kv[0] + off) = v;
          *(uint4*)(sc->kv[1] + off) = v;
        }
        float n2 = bf_lo(v.x) * bf_lo(v.x) + bf_hi(v.x) * bf_hi(v.x) + bf_lo(v.y) * bf_lo(v.y) + bf_hi(v.y) * bf_hi(v.y) +
                   bf_lo(v.z) * bf_lo(v.z) + bf_hi(v.z) * bf_hi(v.z) + bf_lo(v.w) * bf_lo(v.w) + bf_hi(v.w) * bf_hi(v.w);
        n2 += __shfl_xor_sync(~0u, n2, 1);
        const uint32_t mx = __reduce_max_sync(~0u, __float_as_uint(n2) & 0x7FFFFFFFu);
        if (lane == 0) red_max_s(SM_MAX + 4, mx);
        bar_sync(6, 128);
        if (tid == 0) {
          const unsigned long long f = ((unsigned long long)epoch << 32) | lds32(SM_MAX + 4);
          asm volatile("st.release.gpu.global.u64 [%0], %1;" ::"l"(sc->kvflag + 2 * T + c), "l"(f) : "memory");
        }
        TL(1);
      }
      if ((lane & 3) == 0) {
        const uint32_t ad = SM_G + (warp * 16 + (lane >> 2)) * 4;
        sts32(ad, __float_as_uint(__fdividef(1.f, 1.f + __expf(-a[8]))));
        sts32(ad + 32, __float_as_uint(__fdividef(1.f, 1.f + __expf(-a[10]))));
      }
    } else if (wg == 1) {
      unsigned short v[4];
#pragma unroll
      for (int i = 0; i < 4; i++) v[i] = __ldg(gw + i * 128 + tid - 128);
      bar_sync(0, 640);
#pragma unroll
      for (int i = 0; i < 4; i++) asm volatile("st.shared.u16 [%0], %1;" ::"r"(SM_KV + 3 * KVS + (i * 128 + tid - 128) * 16), "h"(v[i]) : "memory");
      fence_async_smem();
      bar_arrive(5, 256);
    } else {
      epoch = sc->epoch[blockIdx.x] + 1;
      if (c < 2) {
#pragma unroll
        for (int i = 0; i < 4; i++) *(uint4*)(sc->ex + T * 32768 + c * 16384 + i * 4096 + (tid - 256) * 16) = make_uint4(~0u, ~0u, ~0u, ~0u);
      }
#pragma unroll
      for (int i = 0; i < 2; i++) sts128(SM_KV + (i * 2 + wg - 2) * KVS + KVB + (tid & 127) * 16, make_uint4(0x3F80u, 0, 0, 0));
      fence_async_smem();
      bar_sync(0, 640);
      if (wg == 3) { TL(26); }
      if (wg == 3 && warp == 0) {
        mbar_wait(SM_XBAR + 0 * 8, 0);
        if (elect()) {
#pragma unroll 1
          for (int u = T >> 4; u < 7; u += 2) tma_prefetch(&maps.m[2 + ((T >> 3) & 1)], 448 * c + 64 * u, (T & 7) * 64);
        }
        __syncwarp();
      }
    }
    bar_sync(1, 640);
    {
      float n0 = 0.f, n1 = 0.f;
#pragma unroll
      for (int p = 0; p < 2; p++) {
        const uint4 v = lds128(SM_Q + p * 8192 + tid * 16);
        float a = bf_lo(v.x) * bf_lo(v.x) + bf_hi(v.x) * bf_hi(v.x) + bf_lo(v.z) * bf_lo(v.z) + bf_hi(v.z) * bf_hi(v.z);
        float b = bf_lo(v.y) * bf_lo(v.y) + bf_hi(v.y) * bf_hi(v.y) + bf_lo(v.w) * bf_lo(v.w) + bf_hi(v.w) * bf_hi(v.w);
        a += __shfl_xor_sync(~0u, a, 1); a += __shfl_xor_sync(~0u, a, 2);
        b += __shfl_xor_sync(~0u, b, 1); b += __shfl_xor_sync(~0u, b, 2);
        if (p == 0) n0 = a, n1 = b;
        else n0 = __uint_as_float(max(__float_as_uint(n0) & 0x7FFFFFFFu, __float_as_uint(a) & 0x7FFFFFFFu)),
             n1 = __uint_as_float(max(__float_as_uint(n1) & 0x7FFFFFFFu, __float_as_uint(b) & 0x7FFFFFFFu));
      }
      const uint32_t mx = __reduce_max_sync(~0u, max(__float_as_uint(n0), __float_as_uint(n1)));
      if (lane == 0) red_max_s(SM_MAX, mx);
    }
    if (wg == 2 && warp == 0) {
      bar_sync(2, 512);
      TLW(2);
      unsigned long long fk, fv;
      bool ok = false;
#pragma unroll 1
      for (int i = 0; i < (1 << 21) && !ok; i++) {
        asm volatile("ld.relaxed.gpu.global.v2.u64 {%0, %1}, [%2];" : "=l"(fk), "=l"(fv) : "l"(sc->kvflag + 2 * lane) : "memory");
        ok = __all_sync(~0u, (uint32_t)(fk >> 32) == epoch && (uint32_t)(fv >> 32) == epoch);
      }
      if (!ok) __trap();
      fence_acquire();
      fence_async();
      const float qm = ldsf(SM_MAX), km = __uint_as_float((uint32_t)fk), vm = __uint_as_float((uint32_t)fv);
      const bool fast = __all_sync(~0u, qm * km * (QSCALE * QSCALE) <= 48.f * 48.f && qm <= 1048576.f && km <= 1048576.f && vm <= 1e30f);
      if (elect()) {
        sts32(SM_MAX + 8, !fast);
#pragma unroll
        for (int i = 0; i < 2; i++) {
          mbar_expect(SM_KBAR + i * 8, KVB);
          bulk_g2s(SM_KV + i * KVS, sc->kv[!fast] + i * KVB, KVB, SM_KBAR + i * 8);
        }
        l2_prefetch(pf_down + blockIdx.x * 14336, 14336);
        l2_prefetch(pf_wo + blockIdx.x * 4096, 4096);
      }
      __syncwarp();
      TLW(3);
    } else {
      bar_arrive(2, 512);
    }
    mbar_wait(SM_KBAR, 0);
    const int safe = __shfl_sync(~0u, lds32(SM_MAX + 8), 0);
    const int duty = wg == warp ? wg : -1;
    auto finish = [&](int pass, const float* o) {
      const uint32_t ga = SM_G + (warp * 16 + (lane >> 2)) * 4;
      const float l0 = __shfl_sync(~0u, o[8], lane & ~3), l1 = __shfl_sync(~0u, o[10], lane & ~3);
      const float r0 = __fdividef(ldsf(ga), l0), r1 = __fdividef(ldsf(ga + 32), l1);
      const uint32_t f0 = pack_bf16(o[0] * r0, o[1] * r0), f1 = pack_bf16(o[2] * r1, o[3] * r1);
      const uint32_t f2 = pack_bf16(o[4] * r0, o[5] * r0), f3 = pack_bf16(o[6] * r1, o[7] * r1);
      if (pass == 0) {
        uint32_t* op = (uint32_t*)(sc->o + blockIdx.x * 8192 + wg * 2048 + warp * 256) + lane;
        op[0] = f0, op[32] = f1, op[256] = f2, op[288] = f3;
        __syncwarp();
        if (lane == 0) mbar_arrive(SM_PBAR);
        TL(4 + wg * 2);
      } else {
        unsigned char* ex = sc->ex + T * 32768 + tid * 16;
        asm volatile("st.relaxed.gpu.global.v4.u32 [%0], {%1,%2,%3,%4};" ::"l"(ex + c * 8192), "r"(f0), "r"(f1), "r"(f2), "r"(f3) : "memory");
        TL(5 + wg * 2);
        const uint32_t ad = SM_X + 32768 + wg * 2048 + (lane >> 4) * 1024 + warp * 256 + (lane & 15) * 16;
        mbar_wait(SM_FBAR, 0);
        stsm4(ad + c * 8192, f0, f1, f2, f3);
        uint4 v[3];
        bool ok = false;
#pragma unroll 1
        for (int i = 0; i < (1 << 21) && !ok; i++) {
          uint32_t m = 0;
#pragma unroll
          for (int j = 0; j < 3; j++) {
            asm volatile("ld.relaxed.gpu.global.v4.u32 {%0,%1,%2,%3}, [%4];" : "=r"(v[j].x), "=r"(v[j].y), "=r"(v[j].z), "=r"(v[j].w)
                         : "l"(ex + ((c + 1 + j) & 3) * 8192) : "memory");
          }
#pragma unroll
          for (int j = 0; j < 3; j++) m = max(max(m, max(v[j].x, v[j].y)), max(v[j].z, v[j].w));
          ok = __all_sync(~0u, m != ~0u);
        }
        if (!ok) __trap();
#pragma unroll
        for (int j = 0; j < 3; j++) stsm4(ad + ((c + 1 + j) & 3) * 8192, v[j].x, v[j].y, v[j].z, v[j].w);
        fence_async_smem();
        __syncwarp();
        if (lane == 0) mbar_arrive(SM_OBAR + wg * 8);
        if (wg == 3) { TL(30); }
      }
    };
    if (!safe) {
#pragma unroll 1
      for (int pass = 0; pass < 2; pass++) {
        float o[12];
        attn_fast(pass, duty, sc->kv[0], cor, d, o);
        finish(pass, o);
      }
    } else {
#pragma unroll 1
      for (int pass = 0; pass < 2; pass++) {
        float o[12];
        attn_safe(pass, duty, sc->kv[1], d, o);
        finish(pass, o);
      }
    }
  }
}

typedef CUresult (*EncodeFn)(CUtensorMap*, CUtensorMapDataType, cuuint32_t, void*, const cuuint64_t*, const cuuint64_t*,
                             const cuuint32_t*, const cuuint32_t*, CUtensorMapInterleave, CUtensorMapSwizzle,
                             CUtensorMapL2promotion, CUtensorMapFloatOOBfill);

void make_map(EncodeFn fn, CUtensorMap* m, void* p, int rank, int rows, int cols, int box_rows) {
  cuuint64_t dims[3] = {(cuuint64_t)(rank == 2 ? cols : 64), (cuuint64_t)rows, (cuuint64_t)cols / 64};
  cuuint64_t strides[2] = {(cuuint64_t)cols * 2, 128};
  cuuint32_t box[3] = {64, (cuuint32_t)box_rows, 2};
  cuuint32_t es[3] = {1, 1, 1};
  fn(m, CU_TENSOR_MAP_DATA_TYPE_BFLOAT16, rank, p, dims, strides, box, es, CU_TENSOR_MAP_INTERLEAVE_NONE,
     CU_TENSOR_MAP_SWIZZLE_128B, CU_TENSOR_MAP_L2_PROMOTION_L2_128B, CU_TENSOR_MAP_FLOAT_OOB_FILL_NONE);
}

}

extern "C" void kernel_launch(void* const* d_in, const int* in_sizes, int n_in, void* d_out, int out_size) {
  static EncodeFn fn = nullptr;
  static Scratch* sc = nullptr;
  if (!fn) {
    void* p = nullptr;
    cudaDriverEntryPointQueryResult st;
    cudaGetDriverEntryPoint("cuTensorMapEncodeTiled", &p, cudaEnableDefault, &st);
    fn = (EncodeFn)p;
    cudaFuncSetAttribute(fused_kernel, cudaFuncAttributeMaxDynamicSharedMemorySize, SM_TOTAL);
    cudaGetSymbolAddress((void**)&sc, g_scratch);
  }
  Maps maps;
  make_map(fn, &maps.m[0], d_in[0], 3, 2048, 512, 64);
  make_map(fn, &maps.m[1], d_in[1], 3, 512, 512, 64);
  make_map(fn, &maps.m[2], d_in[6], 2, 512, 1792, 64);
  make_map(fn, &maps.m[3], d_in[7], 2, 512, 1792, 64);
  make_map(fn, &maps.m[4], d_in[8], 3, 1792, 512, 64);
  make_map(fn, &maps.m[5], d_in[4], 3, 512, 512, 64);
  make_map(fn, &maps.m[6], d_out, 3, 2048, 512, 16);
  const Descs d{mkdesc(SM_KV, 128, 256, 0), mkdesc(SM_KV + 4096, 128, 2048, 0), mkdesc(SM_X, 16, 1024, 1),
                mkdesc(SM_X, 1024, 128, 0), mkdesc(SM_B, 8192, 1024, 1)};
  fused_kernel<<<128, 640, SM_TOTAL>>>(sc, (const __nv_bfloat16*)d_in[2], (const __nv_bfloat16*)d_in[3],
                                       (const unsigned short*)d_in[9], (const unsigned char*)d_in[0], (const unsigned char*)d_in[1],
                                       (const unsigned char*)d_in[8], (const unsigned char*)d_in[4], 0x9F809F80u, d, maps);
}
```

```cpp
#include <cuda_runtime.h>
#include <cuda_bf16.h>
#include <cuda_fp16.h>
#include <cuda.h>
#include <stdint.h>

namespace {

struct Scratch {
  unsigned int epoch[256];
  unsigned long long kvflag[128];
  unsigned int flag[128 * 32];
  unsigned char kv[2][131072];
  unsigned char ex[128 * 8192];
  unsigned char o[128 * 8192];
  unsigned char h[32 * 28 * 8192];
};
__device__ __align__(1024) Scratch g_scratch;
#define TL(i)
#define TLW(i)

struct Maps { CUtensorMap m[7]; };
struct Descs { uint64_t k, v, x, a, b; };

constexpr uint32_t KVB = 8192;
constexpr uint32_t KVS = 10240;
constexpr uint32_t SB = 1024;
constexpr uint32_t SM_X = SB;
constexpr uint32_t SM_B = SM_X + 65536;
constexpr uint32_t SM_KV = SM_B + 65536;
constexpr uint32_t SM_Q = SM_KV + 4 * KVS;
constexpr uint32_t SM_G = SM_Q + 16384;
constexpr uint32_t SM_XBAR = SM_G + 256;
constexpr uint32_t SM_BBAR = SM_XBAR + 32;
constexpr uint32_t SM_KBAR = SM_BBAR + 32;
constexpr uint32_t SM_EBAR = SM_KBAR + 32;
constexpr uint32_t SM_OBAR = SM_EBAR + 32;
constexpr uint32_t SM_FBAR = SM_OBAR + 32;
constexpr uint32_t SM_KEBAR = SM_FBAR + 8;
constexpr uint32_t SM_PBAR = SM_KEBAR + 32;
constexpr uint32_t SM_MAX = SM_PBAR + 8;
constexpr uint32_t SM_TL = SM_MAX + 16;
constexpr uint32_t SM_TOTAL = SM_TL - SB;

__device__ __forceinline__ void wg_fence() { asm volatile("wgmma.fence.sync.aligned;" ::: "memory"); }
__device__ __forceinline__ void wg_commit() { asm volatile("wgmma.commit_group.sync.aligned;" ::: "memory"); }
template <int N> __device__ __forceinline__ void wg_wait() { asm volatile("wgmma.wait_group.sync.aligned %0;" ::"n"(N) : "memory"); }
template <int N> __device__ __forceinline__ void regfence(float* d) {
#pragma unroll
  for (int i = 0; i < N; i++) asm volatile("" : "+f"(d[i])::"memory");
}
template <int N> __device__ __forceinline__ void regfence(uint32_t* d) {
#pragma unroll
  for (int i = 0; i < N; i++) asm volatile("" : "+r"(d[i])::"memory");
}
__host__ __device__ constexpr uint64_t mkdesc(uint32_t addr, uint32_t lbo, uint32_t sbo, int sw) {
  return (uint64_t)((addr & 0x3FFFF) >> 4) | ((uint64_t)(lbo >> 4) << 16) | ((uint64_t)(sbo >> 4) << 32) | ((uint64_t)sw << 62);
}
__device__ __forceinline__ void mbar_init(uint32_t a, uint32_t c) { asm volatile("mbarrier.init.shared::cta.b64 [%0], %1;" ::"r"(a), "r"(c) : "memory"); }
__device__ __forceinline__ void mbar_expect(uint32_t a, uint32_t b) { asm volatile("mbarrier.arrive.expect_tx.shared::cta.b64 _, [%0], %1;" ::"r"(a), "r"(b) : "memory"); }
__device__ __forceinline__ bool mbar_try(uint32_t a, uint32_t ph) {
  uint32_t ok;
  asm volatile("{\n.reg .pred p;\nmbarrier.try_wait.parity.shared::cta.b64 p, [%1], %2;\nselp.u32 %0, 1, 0, p;\n}" : "=r"(ok) : "r"(a), "r"(ph) : "memory");
  return ok;
}
__device__ __forceinline__ void mbar_wait(uint32_t a, uint32_t ph) {
  if (mbar_try(a, ph)) return;
#pragma unroll 1
  for (int i = 0; i < (1 << 20); i++)
    if (mbar_try(a, ph)) return;
  __trap();
}
__device__ __forceinline__ void bulk_g2s(uint32_t dst, const void* src, uint32_t bytes, uint32_t mbar) {
  asm volatile("cp.async.bulk.shared::cluster.global.mbarrier::complete_tx::bytes [%0], [%1], %2, [%3];" ::"r"(dst), "l"(src), "r"(bytes), "r"(mbar) : "memory");
}
__device__ __forceinline__ void tma_load(uint32_t dst, const CUtensorMap* m, int x, int y, uint32_t mbar) {
  asm volatile("cp.async.bulk.tensor.2d.shared::cluster.global.mbarrier::complete_tx::bytes [%0], [%1, {%2, %3}], [%4];" ::"r"(dst), "l"(m), "r"(x), "r"(y), "r"(mbar) : "memory");
}
__device__ __forceinline__ void tma_load3(uint32_t dst, const CUtensorMap* m, int y, int z, uint32_t mbar) {
  asm volatile("cp.async.bulk.tensor.3d.shared::cluster.global.mbarrier::complete_tx::bytes [%0], [%1, {0, %2, %3}], [%4];" ::"r"(dst), "l"(m), "r"(y), "r"(z), "r"(mbar) : "memory");
}
__device__ __forceinline__ void tma_store3(const CUtensorMap* m, int y, int z, uint32_t src) {
  asm volatile("cp.async.bulk.tensor.3d.global.shared::cta.bulk_group [%0, {0, %1, %2}], [%3];" ::"l"(m), "r"(y), "r"(z), "r"(src) : "memory");
}
__device__ __forceinline__ void tma_prefetch(const CUtensorMap* m, int x, int y) {
  asm volatile("cp.async.bulk.prefetch.tensor.2d.L2.global.tile [%0, {%1, %2}];" ::"l"(m), "r"(x), "r"(y) : "memory");
}
__device__ __forceinline__ void l2_prefetch(const void* p, uint32_t bytes) {
  asm volatile("cp.async.bulk.prefetch.L2.global [%0], %1;" ::"l"(p), "r"(bytes) : "memory");
}
__device__ __forceinline__ void fence_async() { asm volatile("fence.proxy.async.global;" ::: "memory"); }
__device__ __forceinline__ void fence_async_smem() { asm volatile("fence.proxy.async.shared::cta;" ::: "memory"); }
__device__ __forceinline__ void fence_acquire() { asm volatile("fence.acquire.gpu;" ::: "memory"); }
__device__ __forceinline__ bool elect() {
  uint32_t r;
  asm volatile("{\n.reg .pred p;\nelect.sync _|p, 0xffffffff;\nselp.u32 %0, 1, 0, p;\n}" : "=r"(r));
  return r;
}
__device__ __forceinline__ void mbar_arrive(uint32_t a) { asm volatile("mbarrier.arrive.shared::cta.b64 _, [%0];" ::"r"(a) : "memory"); }
__device__ __forceinline__ void bar_sync(int id, int n) { asm volatile("bar.sync %0, %1;" ::"r"(id), "r"(n) : "memory"); }
__device__ __forceinline__ void bar_arrive(int id, int n) { asm volatile("bar.arrive %0, %1;" ::"r"(id), "r"(n) : "memory"); }
__device__ __forceinline__ void red_max_s(uint32_t a, uint32_t v) { asm volatile("red.shared::cta.max.u32 [%0], %1;" ::"r"(a), "r"(v) : "memory"); }
__device__ __forceinline__ uint32_t lds32(uint32_t a) { uint32_t r; asm volatile("ld.shared.u32 %0, [%1];" : "=r"(r) : "r"(a) : "memory"); return r; }
__device__ __forceinline__ float ldsf(uint32_t a) { return __uint_as_float(lds32(a)); }
__device__ __forceinline__ void sts32(uint32_t a, uint32_t v) { asm volatile("st.shared.u32 [%0], %1;" ::"r"(a), "r"(v) : "memory"); }
__device__ __forceinline__ uint4 lds128(uint32_t a) {
  uint4 r;
  asm volatile("ld.shared.v4.u32 {%0,%1,%2,%3}, [%4];" : "=r"(r.x), "=r"(r.y), "=r"(r.z), "=r"(r.w) : "r"(a) : "memory");
  return r;
}
__device__ __forceinline__ void sts128(uint32_t a, uint4 v) { asm volatile("st.shared.v4.u32 [%0], {%1,%2,%3,%4};" ::"r"(a), "r"(v.x), "r"(v.y), "r"(v.z), "r"(v.w) : "memory"); }
__device__ __forceinline__ uint32_t pack_bf16(float lo, float hi) { uint32_t r; asm("cvt.rn.bf16x2.f32 %0, %1, %2;" : "=r"(r) : "f"(hi), "f"(lo)); return r; }
__device__ __forceinline__ uint32_t pack_f16(float lo, float hi) { uint32_t r; asm("cvt.rn.f16x2.f32 %0, %1, %2;" : "=r"(r) : "f"(hi), "f"(lo)); return r; }
__device__ __forceinline__ float bf_lo(uint32_t v) { return __uint_as_float(v << 16); }
__device__ __forceinline__ float bf_hi(uint32_t v) { return __uint_as_float(v & 0xFFFF0000u); }
__device__ __forceinline__ float ex2(float a) { float x; asm("ex2.approx.ftz.f32 %0, %1;" : "=f"(x) : "f"(a)); return x; }
__device__ __forceinline__ uint32_t ld_relaxed(const unsigned int* p) {
  uint32_t v;
  asm volatile("ld.relaxed.gpu.global.u32 %0, [%1];" : "=r"(v) : "l"(p) : "memory");
  return v;
}
__device__ __forceinline__ uint4 ld_relaxed4(const void* p) {
  uint4 v;
  asm volatile("ld.relaxed.gpu.global.v4.u32 {%0,%1,%2,%3}, [%4];" : "=r"(v.x), "=r"(v.y), "=r"(v.z), "=r"(v.w) : "l"(p) : "memory");
  return v;
}
__device__ __forceinline__ void wait_flag(const unsigned int* p, uint32_t v, uint32_t target) {
#pragma unroll 1
  for (int i = 0; i < (1 << 21) && (int)(v - target) < 0; i++) v = ld_relaxed(p);
  if ((int)(v - target) < 0) __trap();
  fence_acquire();
  fence_async();
}
__device__ __forceinline__ void stsm4(uint32_t a, uint32_t r0, uint32_t r1, uint32_t r2, uint32_t r3) {
  asm volatile("stmatrix.sync.aligned.m8n8.x4.shared.b16 [%0], {%1,%2,%3,%4};" ::"r"(a), "r"(r0), "r"(r1), "r"(r2), "r"(r3) : "memory");
}

#define R4(d, i) "+f"(d[i]), "+f"(d[i + 1]), "+f"(d[i + 2]), "+f"(d[i + 3])
#define R8(d, i) R4(d, i), R4(d, i + 4)
#define R32(d, i) R8(d, i), R8(d, i + 8), R8(d, i + 16), R8(d, i + 24)
#define L4 "%0,%1,%2,%3"
#define L8 L4 ",%4,%5,%6,%7"
#define L12 L8 ",%8,%9,%10,%11"
#define L32 L12 ",%12,%13,%14,%15,%16,%17,%18,%19,%20,%21,%22,%23,%24,%25,%26,%27,%28,%29,%30,%31"
#define L64 L32 ",%32,%33,%34,%35,%36,%37,%38,%39,%40,%41,%42,%43,%44,%45,%46,%47,%48,%49,%50,%51,%52,%53,%54,%55,%56,%57,%58,%59,%60,%61,%62,%63"
__device__ __forceinline__ void mma_ss128(float* d, uint64_t da, uint64_t db, int sd) {
  asm volatile("{\n.reg .pred p;\nsetp.ne.b32 p, %66, 0;\nwgmma.mma_async.sync.aligned.m64n128k16.f32.bf16.bf16 {" L64 "}, %64, %65, p, 1, 1, 0, 1;\n}\n"
               : R32(d, 0), R32(d, 32) : "l"(da), "l"(db), "r"(sd));
}
__device__ __forceinline__ void mma_ss24(float* d, uint64_t da, uint64_t db) {
  asm volatile("wgmma.mma_async.sync.aligned.m64n24k16.f32.bf16.bf16 {" L12 "}, %12, %13, 1, 1, 1, 0, 1;\n" : R8(d, 0), R4(d, 8) : "l"(da), "l"(db));
}
__device__ __forceinline__ void mma_qk_f16(float* d, const uint32_t* a, uint64_t db) {
  asm volatile("wgmma.mma_async.sync.aligned.m64n64k16.f32.f16.f16 {" L32 "}, {%32,%33,%34,%35}, %36, 1, 1, 1, 0;\n"
               : R32(d, 0) : "r"(a[0]), "r"(a[1]), "r"(a[2]), "r"(a[3]), "l"(db));
}
__device__ __forceinline__ void mma_qk_bf16(float* d, const uint32_t* a, uint64_t db) {
  asm volatile("wgmma.mma_async.sync.aligned.m64n64k16.f32.bf16.bf16 {" L32 "}, {%32,%33,%34,%35}, %36, 0, 1, 1, 0;\n"
               : R32(d, 0) : "r"(a[0]), "r"(a[1]), "r"(a[2]), "r"(a[3]), "l"(db));
}
__device__ __forceinline__ void mma_pv(float* d, const uint32_t* a, uint64_t db) {
  asm volatile("wgmma.mma_async.sync.aligned.m64n24k16.f32.bf16.bf16 {" L12 "}, {%12,%13,%14,%15}, %16, 1, 1, 1, 1;\n"
               : R8(d, 0), R4(d, 8) : "r"(a[0]), "r"(a[1]), "r"(a[2]), "r"(a[3]), "l"(db));
}

__device__ __forceinline__ uint32_t exp_mufu(float a, float b) { return pack_bf16(ex2(a), ex2(b)); }
constexpr float EXP_MAGIC = 446.0f + 0.00390625f - 0.5860f;
#define PM 0x5555u
constexpr uint32_t POLY_MASK = PM;
__device__ __forceinline__ uint32_t exp_soft(float t0, float t1, uint32_t cor) {
  uint32_t y = __byte_perm(__float_as_uint(t0), __float_as_uint(t1), 0x6521);
  uint32_t u, r;
  asm("lop3.b32 %0, %1, 0x007F007F, %2, 0xEA;" : "=r"(u) : "r"(y), "r"(cor));
  uint32_t e = y - u;
  asm("fma.rn.bf16x2 %0, %1, %2, %3;" : "=r"(r) : "r"(y), "r"(u), "r"(e));
  return r;
}
constexpr float QSCALE = 0.25f * 1.4426950408889634f;

__host__ __device__ constexpr uint32_t off_k(int h) { return ((h >> 1) * KVS + (h & 1) * 2048) >> 4; }
__host__ __device__ constexpr uint32_t off_v(int h) { return ((h >> 1) * KVS + (h & 1) * 1024) >> 4; }

__device__ __forceinline__ void kv_advance(int sl, int it, int duty, const unsigned char* src) {
  if ((threadIdx.x & 31) == 0) mbar_arrive(SM_KEBAR + ((sl + 3) & 3) * 8);
  if (duty == sl) {
    const int t = (sl + 2) & 3;
    mbar_wait(SM_KEBAR + t * 8, (sl == 0 ? it + 1 : it) & 1);
    if (elect()) {
      mbar_expect(SM_KBAR + t * 8, KVB);
      bulk_g2s(SM_KV + t * KVS, src + ((4 * it + sl + 2) & 15) * KVB, KVB, SM_KBAR + t * 8);
    }
  }
}

__device__ __forceinline__ void attn_fast(int pass, int duty, const unsigned char* src, uint32_t cor, const Descs& d, float* o) {
  uint32_t q[4], p[16];
  float s[32];
  {
    const uint4 v = lds128(SM_Q + pass * 8192 + threadIdx.x * 16);
    q[0] = v.x, q[1] = v.y, q[2] = v.z, q[3] = v.w;
#pragma unroll
    for (int i = 0; i < 4; i++) q[i] = pack_f16(bf_lo(q[i]) * QSCALE, bf_hi(q[i]) * QSCALE);
  }
#pragma unroll
  for (int i = 0; i < 12; i++) o[i] = 0.f;
#pragma unroll
  for (int j = 0; j < 32; j++) s[j] = ((POLY_MASK >> (j / 2)) & 1) ? EXP_MAGIC : 0.f;
  regfence<12>(o); regfence<32>(s); regfence<4>(q);
#pragma unroll 1
  for (int it = 0; it < 4; it++) {
    if (pass + it == 4 && duty >= 2) duty = -1;
    mbar_wait(SM_KBAR, it & 1);
    wg_fence();
    mma_qk_f16(s, q, d.k);
    wg_commit();
#pragma unroll
    for (int h = 0; h < 8; h++) {
      wg_wait<0>();
      regfence<32>(s);
      if ((h & 1) == 0) kv_advance(h >> 1, it, duty, src);
#pragma unroll
      for (int j = 0; j < 16; j++)
        p[j] = ((POLY_MASK >> j) & 1) ? exp_soft(s[2 * j], s[2 * j + 1], cor) : exp_mufu(s[2 * j], s[2 * j + 1]);
      if (h < 7 && (h & 1)) mbar_wait(SM_KBAR + ((h + 1) >> 1) * 8, it & 1);
      wg_fence();
#pragma unroll
      for (int i = 0; i < 4; i++) mma_pv(o, p + 4 * i, d.v + off_v(h) + i * 16);
      if (h < 7) mma_qk_f16(s, q, d.k + off_k(h + 1));
      wg_commit();
    }
  }
  wg_wait<0>();
  regfence<12>(o); regfence<32>(s);
}

__device__ __forceinline__ void attn_safe(int pass, int duty, const unsigned char* src, const Descs& d, float* o) {
  uint32_t q[4], p[16];
  float s[32];
  float m0 = -INFINITY, m1 = -INFINITY;
  {
    const uint4 v = lds128(SM_Q + pass * 8192 + threadIdx.x * 16);
    q[0] = v.x, q[1] = v.y, q[2] = v.z, q[3] = v.w;
  }
#pragma unroll
  for (int i = 0; i < 12; i++) o[i] = 0.f;
#pragma unroll
  for (int j = 0; j < 32; j++) s[j] = 0.f;
  regfence<12>(o); regfence<32>(s); regfence<4>(q);
#pragma unroll 1
  for (int i = 0; i < 32; i++) {
    const int h = i & 7, it = i >> 3;
    if (pass + it == 4 && duty >= 2) duty = -1;
    mbar_wait(SM_KBAR + (h >> 1) * 8, ~it & 1);
    wg_fence();
    mma_qk_bf16(s, q, d.k + off_k(h));
    wg_commit();
    wg_wait<0>();
    regfence<32>(s); regfence<12>(o);
    if ((h & 1) == 0) kv_advance(h >> 1, it, duty, src);
    float n0 = m0, n1 = m1;
#pragma unroll
    for (int j = 0; j < 16; j++) {
      const uint32_t r = pack_bf16(s[2 * j], s[2 * j + 1]);
      s[2 * j] = bf_lo(r), s[2 * j + 1] = bf_hi(r);
      if (j & 1) n1 = fmaxf(n1, fmaxf(s[2 * j], s[2 * j + 1])); else n0 = fmaxf(n0, fmaxf(s[2 * j], s[2 * j + 1]));
    }
    n0 = fmaxf(n0, __shfl_xor_sync(~0u, n0, 1)); n0 = fmaxf(n0, __shfl_xor_sync(~0u, n0, 2));
    n1 = fmaxf(n1, __shfl_xor_sync(~0u, n1, 1)); n1 = fmaxf(n1, __shfl_xor_sync(~0u, n1, 2));
    const float a0 = ex2((m0 - n0) * QSCALE), a1 = ex2((m1 - n1) * QSCALE);
    m0 = n0, m1 = n1;
#pragma unroll
    for (int j = 0; j < 12; j++) o[j] *= (j & 2) ? a1 : a0;
#pragma unroll
    for (int j = 0; j < 16; j++) {
      const float m = (j & 1) ? m1 : m0;
      p[j] = exp_mufu((s[2 * j] - m) * QSCALE, (s[2 * j + 1] - m) * QSCALE);
    }
    regfence<12>(o);
    wg_fence();
#pragma unroll
    for (int j = 0; j < 4; j++) mma_pv(o, p + 4 * j, d.v + off_v(h) + j * 16);
    wg_commit();
  }
  wg_wait<0>();
  regfence<12>(o); regfence<32>(s);
}

__global__ void __launch_bounds__(640, 1)
fused_kernel(Scratch* __restrict__ sc, const __nv_bfloat16* __restrict__ wk, const __nv_bfloat16* __restrict__ wv,
             const unsigned short* __restrict__ gw, const unsigned char* __restrict__ pf_x, const unsigned char* __restrict__ pf_wq,
             const unsigned char* __restrict__ pf_down, const unsigned char* __restrict__ pf_wo, uint32_t cor,
             const __grid_constant__ Descs d, const __grid_constant__ Maps maps) {
  extern __shared__ __align__(1024) unsigned char smem[];
  const int tid = threadIdx.x, wid = __shfl_sync(~0u, tid >> 5, 0), wg = wid >> 2, warp = wid & 3, lane = tid & 31;
  const int T = blockIdx.x >> 2, c = blockIdx.x & 3;
  if (tid == 0) { TLW(63); }

  uint4 wv0, wv1;
  unsigned short gv = 0;
  uint32_t ep = 0;
  if (tid < 512) {
    if (c < 2) wv0 = __ldg((const uint4*)(c == 0 ? wk : wv) + tid), wv1 = __ldg((const uint4*)(c == 0 ? wk : wv) + 512 + tid);
    gv = __ldg(gw + tid);
    if (wid < 4 || wid == 12) ep = ld_relaxed(sc->epoch + blockIdx.x);
  }
  if (wid == 16) {
    if (elect()) {
      l2_prefetch(pf_x + blockIdx.x * 16384, 16384);
#pragma unroll
      for (int i = 0; i < 8; i++) mbar_init(SM_XBAR + 8 * i, 1);
      asm volatile("fence.mbarrier_init.release.cluster;" ::: "memory");
#pragma unroll
      for (int i = 0; i < 4; i++) {
        mbar_expect(SM_XBAR + 8 * i, 16384);
        tma_load3(SM_X + i * 16384, &maps.m[0], 64 * T, 2 * i, SM_XBAR + 8 * i);
      }
      l2_prefetch(pf_wq + blockIdx.x * 4096, 4096);
#pragma unroll
      for (int i = 0; i < 4; i++) {
        mbar_expect(SM_BBAR + 8 * i, 16384);
        tma_load3(SM_B + i * 16384, &maps.m[1], 64 * i, 2 * c, SM_BBAR + 8 * i);
      }
    }
    __syncwarp();
    TLW(29);
  }
  if (wid == 17) {
    if (elect()) {
#pragma unroll
      for (int i = 8; i < 26; i++) mbar_init(SM_XBAR + 8 * i, i < 12 ? 1 : i < 21 ? 4 : 16);
      sts32(SM_MAX, 0);
      asm volatile("fence.mbarrier_init.release.cluster;" ::: "memory");
#pragma unroll
      for (int i = 2; i < 7; i++) asm volatile("prefetch.tensormap [%0];" ::"l"(&maps.m[i]) : "memory");
      if ((uint32_t)__cvta_generic_to_shared(smem) != SB) __trap();
    }
    __syncwarp();
  }
  TL(32 + wg);
  if (tid < 512) {
    sts128(SM_KV + wg * KVS + KVB + (tid & 127) * 16, make_uint4(0x3F80u, 0, 0, 0));
    if (c < 2) {
      sts128(SM_KV + KVS + (tid & 1) * KVS + (tid >> 1) * 16, wv0);
      sts128(SM_KV + KVS + (tid & 1) * KVS + (tid >> 1) * 16 + 4096, wv1);
    }
    asm volatile("st.shared.u16 [%0], %1;" ::"r"(SM_KV + 3 * KVS + tid * 16), "h"(gv) : "memory");
    TL(37 + wg);
    fence_async_smem();
  }
  TL(42 + wg);
  if (wg == 4) { TLW(46 + warp); }
  bar_sync(0, 640);

  if (wg == 4) {
    float acc[64];
    auto stage = [&](int sl, uint32_t ph, uint64_t da, int ka, bool first) {
      mbar_wait(SM_BBAR + sl * 8, ph);
      wg_fence();
      mma_ss128(acc, da, d.b + sl * 1024, !first);
#pragma unroll
      for (int k = 1; k < 4; k++) mma_ss128(acc, da + k * ka, d.b + sl * 1024 + k * 128, 1);
      wg_commit();
    };
    auto release = [&](int sl, uint32_t ph) {
      if (lane == 0) mbar_arrive(SM_EBAR + sl * 8);
      if (warp != sl) return false;
      mbar_wait(SM_EBAR + sl * 8, ph);
      return true;
    };
    const uint32_t bbar = SM_BBAR + warp * 8, bdst = SM_B + warp * 16384;
    auto load_w = [&](int m, int y) {
      if (elect()) {
        mbar_expect(bbar, 16384);
        tma_load3(bdst, &maps.m[m], y, 2 * c, bbar);
      }
    };
    auto load_gu = [&](int x, int y) {
      if (elect()) {
        mbar_expect(bbar, 16384);
        tma_load(bdst, &maps.m[2], x, y, bbar);
        tma_load(bdst + 8192, &maps.m[3], x, y, bbar);
      }
    };
    auto load_aw = [&](const unsigned char* a, int m, int y) {
      if (elect()) {
        mbar_expect(bbar, 24576);
        bulk_g2s(SM_X + warp * 8192, a, 8192, bbar);
        tma_load3(bdst, &maps.m[m], y, 2 * c, bbar);
      }
    };
    auto signal = [&](uint32_t v) {
      if (elect()) asm volatile("st.release.gpu.global.u32 [%0], %1;" ::"l"(sc->flag + blockIdx.x * 32), "r"(v) : "memory");
    };
    const unsigned int* pflag = sc->flag + (T * 4 + warp) * 32;
    const unsigned char* hsrc = sc->h + (T * 4 + warp) * 7 * 8192;
    uint32_t fv = 0;
    if (c < 2) bar_sync(7, 256);
#pragma unroll
    for (int kb = 0; kb < 9; kb++) {
      if (kb < 8) {
        if ((kb & 1) == 0) mbar_wait(SM_XBAR + kb * 4, 0);
        stage(kb & 3, kb >> 2, d.x + kb * 512, 2, kb == 0);
      }
      if (kb > 0) {
        if (kb < 8) wg_wait<1>(); else wg_wait<0>();
        if (release((kb - 1) & 3, (kb - 1) >> 2)) {
          if (kb < 5) load_w(1, (kb + 3) * 64);
          else load_gu(448 * c, warp * 64);
        }
      }
    }
    regfence<64>(acc);
#pragma unroll
    for (int h = 0; h < 8; h++)
      sts128(SM_Q + h * 2048 + (tid - 512) * 16,
             make_uint4(pack_bf16(acc[8 * h], acc[8 * h + 1]), pack_bf16(acc[8 * h + 2], acc[8 * h + 3]),
                        pack_bf16(acc[8 * h + 4], acc[8 * h + 5]), pack_bf16(acc[8 * h + 6], acc[8 * h + 7])));
    bar_arrive(1, 608);
    TL(12);
    const uint32_t epoch = ld_relaxed(sc->epoch + blockIdx.x) + 1;
#pragma unroll 1
    for (int u = 0; u < 7; u++) {
      const int x = 448 * c + 64 * u;
#pragma unroll
      for (int kb = 0; kb < 9; kb++) {
        if (kb < 8) stage(kb & 3, kb >> 2, d.x + kb * 512, 2, kb == 0);
        if (kb > 0) {
          if (kb < 8) wg_wait<1>(); else wg_wait<0>();
          if (release((kb - 1) & 3, (kb - 1) >> 2)) {
            if (kb < 5) {
              load_gu(x, (kb + 3) * 64);
              if (kb == 1 && u == 5) signal(2 * epoch - 1);
              if (u == 6) fv = ld_relaxed(pflag);
            } else if (u < 6) {
              load_gu(x + 64, (kb - 5) * 64);
            } else {
              wait_flag(pflag, fv, 2 * epoch - 1);
              load_aw(hsrc, 4, warp * 448);
            }
          }
        }
      }
      regfence<64>(acc);
      uint32_t* hp = (uint32_t*)(sc->h + (blockIdx.x * 7 + u) * 8192 + warp * 256) + lane;
#pragma unroll
      for (int j = 0; j < 16; j++) {
        float h[2];
#pragma unroll
        for (int e = 0; e < 2; e++) {
          const float x = acc[2 * j + e];
          float t;
          asm("tanh.approx.f32 %0, %1;" : "=f"(t) : "f"(x * fmaf(x * x, 0.044715f * 0.7978845608028654f, 0.7978845608028654f)));
          const float w = x * acc[32 + 2 * j + e];
          h[e] = fmaf(w, t, w);
        }
        hp[(j >> 1) * 256 + (j & 1) * 32] = pack_bf16(h[0], h[1]);
      }
      if (u == 0) {
#pragma unroll
        for (int i = 0; i < 4; i++) *(uint4*)(sc->ex + blockIdx.x * 8192 + i * 2048 + (tid - 512) * 16) = make_uint4(~0u, ~0u, ~0u, ~0u);
        if (warp == 3 && elect()) {
          l2_prefetch(pf_down + blockIdx.x * 14336, 14336);
          l2_prefetch(pf_wo + blockIdx.x * 4096, 4096);
        }
      }
      __syncwarp();
      TL(13 + u);
    }
    if (lane == 0) mbar_arrive(SM_FBAR);
    const unsigned char* osrc = sc->o + (T * 4 + warp) * 8192;
#pragma unroll 1
    for (int g = 0; g < 7; g++) {
#pragma unroll
      for (int j = 0; j < 4; j++) {
        stage(j, g & 1, d.a + j * 512, 128, g == 0 && j == 0);
        wg_wait<1>();
        const int n = j == 0 ? g : g + 1;
        if ((j > 0 || g > 0) && release((j + 3) & 3, (n + 1) & 1)) {
          if (n == 5) wait_flag(pflag, fv, 2 * epoch);
          if (n < 7) load_aw(hsrc + n * 8192, 4, warp * 448 + n * 64); else load_aw(osrc, 5, warp * 128);
          if (n == 4) fv = ld_relaxed(pflag);
          if (j == 1 && n == 2) {
            mbar_wait(SM_PBAR, 0);
            signal(2 * epoch);
          }
        }
      }
    }
    wg_wait<0>();
    if (release(3, 0)) load_aw(osrc, 5, warp * 128);
    regfence<64>(acc);
    TL(20);
    {
      const uint32_t ad = SM_G + (warp * 16 + (lane >> 2)) * 4;
      const float s0 = 0.5f - 0.5f * ldsf(ad), s1 = 0.5f - 0.5f * ldsf(ad + 32);
#pragma unroll
      for (int j = 0; j < 64; j++) acc[j] *= (j & 2) ? s1 : s0;
      regfence<64>(acc);
    }
#pragma unroll
    for (int j = 0; j < 5; j++) {
      if (j < 4) stage(j, 1, d.a + j * 512, 128, false);
      if (j > 0) {
        if (j < 4) wg_wait<1>(); else wg_wait<0>();
        if (release(j - 1, 1)) load_w(5, warp * 128 + 64);
      }
    }
    TL(21);
#pragma unroll
    for (int j = 0; j < 4; j++) mbar_wait(SM_BBAR + j * 8, 0);
    if (tid == 512) sc->epoch[blockIdx.x] = epoch;
    TL(22);
#pragma unroll
    for (int w = 0; w < 4; w++) {
      mbar_wait(SM_OBAR + w * 8, 0);
      wg_fence();
#pragma unroll
      for (int j = 0; j < 4; j++) mma_ss128(acc, d.a + (4 + j) * 512 + w * 128, d.b + j * 1024 + w * 128, 1);
      wg_commit();
    }
    TL(23);
    wg_wait<0>();
    regfence<64>(acc);
    TL(24);
    {
      const int r = (lane & 7) + (lane & 8);
      const uint32_t wb = SM_Q + warp * 4096;
#pragma unroll
      for (int j = 0; j < 8; j++) {
        const int blk = 2 * j + (lane >> 4);
        stsm4(wb + (blk >> 3) * 2048 + r * 128 + (((blk & 7) ^ (r & 7)) << 4),
              pack_bf16(acc[8 * j], acc[8 * j + 1]), pack_bf16(acc[8 * j + 2], acc[8 * j + 3]),
              pack_bf16(acc[8 * j + 4], acc[8 * j + 5]), pack_bf16(acc[8 * j + 6], acc[8 * j + 7]));
      }
      fence_async_smem();
      __syncwarp();
      if (elect()) {
        tma_store3(&maps.m[6], 64 * T + 16 * warp, 2 * c, wb);
        asm volatile("cp.async.bulk.commit_group;" ::: "memory");
        asm volatile("cp.async.bulk.wait_group.read 0;" ::: "memory");
      }
    }
    TL(25);
  } else {
    if (wg == 0) {
      TL(31);
      float a[12];
#pragma unroll
      for (int i = 0; i < 12; i++) a[i] = 0.f;
      constexpr uint64_t dw = mkdesc(SM_KV + KVS, 128, KVS, 0);
      regfence<12>(a);
#pragma unroll
      for (int kb = 0; kb < 4; kb++) {
        mbar_wait(SM_XBAR + kb * 8, 0);
        if (kb == 0) { TL(27); }
        if (kb == 3) { TL(28); }
        wg_fence();
#pragma unroll
        for (int k = 0; k < 8; k++) mma_ss24(a, d.x + kb * 1024 + (k >> 2) * 512 + (k & 3) * 2, dw + (kb * 8 + k) * 16);
        wg_commit();
      }
      wg_wait<0>();
      regfence<12>(a);
      TL(0);
      if (c < 2) {
        bar_arrive(7, 256);
        const uint32_t ad = SM_KV + (warp * 16 + (lane >> 2)) * 32 + (lane & 3) * 4;
        sts32(ad, pack_bf16(a[0], a[1]));
        sts32(ad + 256, pack_bf16(a[2], a[3]));
        sts32(ad + 16, pack_bf16(a[4], a[5]));
        sts32(ad + 272, pack_bf16(a[6], a[7]));
        bar_sync(6, 128);
        TL(54);
        const int r = tid >> 1, hb = tid & 1, j = r >> 1, kk = (j & 1) * 64 + 2 * T + (r & 1);
        const uint4 v = lds128(SM_KV + tid * 16);
        if (c == 0) {
          uint4 w = make_uint4(0, 0, 0, 0);
          if (r >= 2) w = lds128(SM_KV + tid * 16 - 64);
          uint4 e;
          e.x = pack_f16(bf_lo(v.x) - bf_lo(w.x), bf_hi(v.x) - bf_hi(w.x));
          e.y = pack_f16(bf_lo(v.y) - bf_lo(w.y), bf_hi(v.y) - bf_hi(w.y));
          e.z = pack_f16(bf_lo(v.z) - bf_lo(w.z), bf_hi(v.z) - bf_hi(w.z));
          e.w = pack_f16(bf_lo(v.w) - bf_lo(w.w), bf_hi(v.w) - bf_hi(w.w));
          const int off = (j >> 1) * KVB + (kk >> 3) * 256 + hb * 128 + (kk & 7) * 16;
          *(uint4*)(sc->kv[0] + off) = e;
          *(uint4*)(sc->kv[1] + off) = v;
        } else {
          const int off = (j >> 1) * KVB + 4096 + hb * 2048 + kk * 16;
          *(uint4*)(sc->kv[0] + off) = v;
          *(uint4*)(sc->kv[1] + off) = v;
        }
        float n2 = bf_lo(v.x) * bf_lo(v.x) + bf_hi(v.x) * bf_hi(v.x) + bf_lo(v.y) * bf_lo(v.y) + bf_hi(v.y) * bf_hi(v.y) +
                   bf_lo(v.z) * bf_lo(v.z) + bf_hi(v.z) * bf_hi(v.z) + bf_lo(v.w) * bf_lo(v.w) + bf_hi(v.w) * bf_hi(v.w);
        n2 += __shfl_xor_sync(~0u, n2, 1);
        const uint32_t mx = __reduce_max_sync(~0u, __float_as_uint(n2) & 0x7FFFFFFFu);
        TL(55);
        if (lane == 0) {
          const uint32_t b = c == 0 ? mx : __uint_as_float(mx) <= 1e30f ? 0 : 0x7FFFFFFFu;
          asm volatile("red.relaxed.gpu.global.max.u64 [%0], %1;" ::"l"(sc->kvflag + 1), "l"(((unsigned long long)(ep + 1) << 32) | b) : "memory");
          asm volatile("red.release.gpu.global.add.u64 [%0], 1;" ::"l"(sc->kvflag) : "memory");
        }
        __syncwarp();
        TL(1);
      }
      if ((lane & 3) == 0) {
        const uint32_t ad = SM_G + (warp * 16 + (lane >> 2)) * 4;
        sts32(ad, __float_as_uint(__fdividef(1.f, 1.f + __expf(-a[8]))));
        sts32(ad + 32, __float_as_uint(__fdividef(1.f, 1.f + __expf(-a[10]))));
      }
    } else if (wid == 12) {
      TLW(26);
      mbar_wait(SM_XBAR + 0 * 8, 0);
      if (elect()) {
#pragma unroll 1
        for (int u = T >> 4; u < 7; u += 2) tma_prefetch(&maps.m[2 + ((T >> 3) & 1)], 448 * c + 64 * u, (T & 7) * 64);
      }
      __syncwarp();
      uint4 f;
      const uint32_t target = (ep + 1) << 8;
#pragma unroll 1
      for (int i = 0; i < (1 << 21); i++) {
        f = ld_relaxed4(sc->kvflag);
        if (f.x == target) break;
      }
      if (f.x != target) __trap();
      fence_acquire();
      fence_async();
      if (elect()) {
#pragma unroll
        for (int i = 0; i < 2; i++) {
          mbar_expect(SM_KBAR + i * 8, KVB);
          bulk_g2s(SM_KV + i * KVS, sc->kv[0] + i * KVB, KVB, SM_KBAR + i * 8);
        }
        sts32(SM_MAX + 4, f.z);
      }
      __syncwarp();
      TLW(3);
    }
    if (wid != 12) {
      bar_sync(1, 608);
      uint32_t m = 0;
#pragma unroll 1
      for (int p = wid == 13 ? 0 : 1; p < 2; p++) {
#pragma unroll
        for (int i = 0; i < 2; i++) {
          const uint4 v = lds128(SM_Q - 512 + p * 512 + i * 8192 + tid * 16);
          float a = bf_lo(v.x) * bf_lo(v.x) + bf_hi(v.x) * bf_hi(v.x) + bf_lo(v.z) * bf_lo(v.z) + bf_hi(v.z) * bf_hi(v.z);
          float b = bf_lo(v.y) * bf_lo(v.y) + bf_hi(v.y) * bf_hi(v.y) + bf_lo(v.w) * bf_lo(v.w) + bf_hi(v.w) * bf_hi(v.w);
          a += __shfl_xor_sync(~0u, a, 1), b += __shfl_xor_sync(~0u, b, 1);
          a += __shfl_xor_sync(~0u, a, 2), b += __shfl_xor_sync(~0u, b, 2);
          m = max(m, max(__float_as_uint(a) & 0x7FFFFFFFu, __float_as_uint(b) & 0x7FFFFFFFu));
        }
      }
      m = __reduce_max_sync(~0u, m);
      if (lane == 0) red_max_s(SM_MAX, m);
    }
    bar_sync(2, 512);
    if (wg == 2) { TL(2); }
    const float qm = ldsf(SM_MAX), km = ldsf(SM_MAX + 4);
    const bool fast = __all_sync(~0u, qm * km * (QSCALE * QSCALE) <= 48.f * 48.f && qm <= 1048576.f && km <= 1048576.f);
    const int duty = wg == warp ? wg : -1;
    auto finish = [&](int pass, const float* o) {
      const uint32_t ga = SM_G + (warp * 16 + (lane >> 2)) * 4;
      const float l0 = __shfl_sync(~0u, o[8], lane & ~3), l1 = __shfl_sync(~0u, o[10], lane & ~3);
      const float r0 = __fdividef(ldsf(ga), l0), r1 = __fdividef(ldsf(ga + 32), l1);
      const uint32_t f0 = pack_bf16(o[0] * r0, o[1] * r0), f1 = pack_bf16(o[2] * r1, o[3] * r1);
      const uint32_t f2 = pack_bf16(o[4] * r0, o[5] * r0), f3 = pack_bf16(o[6] * r1, o[7] * r1);
      if (pass == 0) {
        uint32_t* op = (uint32_t*)(sc->o + blockIdx.x * 8192 + wg * 2048 + warp * 256) + lane;
        op[0] = f0, op[32] = f1, op[256] = f2, op[288] = f3;
        __syncwarp();
        if (lane == 0) mbar_arrive(SM_PBAR);
        TL(4 + wg * 2);
      } else {
        unsigned char* ex = sc->ex + T * 32768 + tid * 16;
        mbar_wait(SM_FBAR, 0);
        asm volatile("st.relaxed.gpu.global.v4.u32 [%0], {%1,%2,%3,%4};" ::"l"(ex + c * 8192), "r"(f0), "r"(f1), "r"(f2), "r"(f3) : "memory");
        TL(5 + wg * 2);
        const uint32_t ad = SM_X + 32768 + wg * 2048 + (lane >> 4) * 1024 + warp * 256 + (lane & 15) * 16;
        stsm4(ad + c * 8192, f0, f1, f2, f3);
        uint4 v[3];
        bool ok = false;
#pragma unroll 1
        for (int i = 0; i < (1 << 21) && !ok; i++) {
          uint32_t m = 0;
#pragma unroll
          for (int j = 0; j < 3; j++) {
            asm volatile("ld.relaxed.gpu.global.v4.u32 {%0,%1,%2,%3}, [%4];" : "=r"(v[j].x), "=r"(v[j].y), "=r"(v[j].z), "=r"(v[j].w)
                         : "l"(ex + ((c + 1 + j) & 3) * 8192) : "memory");
          }
#pragma unroll
          for (int j = 0; j < 3; j++) m = max(max(m, max(v[j].x, v[j].y)), max(v[j].z, v[j].w));
          ok = __all_sync(~0u, m != ~0u);
        }
        if (!ok) __trap();
#pragma unroll
        for (int j = 0; j < 3; j++) stsm4(ad + ((c + 1 + j) & 3) * 8192, v[j].x, v[j].y, v[j].z, v[j].w);
        fence_async_smem();
        __syncwarp();
        if (lane == 0) mbar_arrive(SM_OBAR + wg * 8);
        if (wg == 3) { TL(30); }
      }
    };
    if (fast) {
#pragma unroll 1
      for (int pass = 0; pass < 2; pass++) {
        float o[12];
        attn_fast(pass, duty, sc->kv[0], cor, d, o);
        finish(pass, o);
      }
    } else {
      if (tid == 384) {
#pragma unroll
        for (int i = 0; i < 2; i++) {
          mbar_wait(SM_KBAR + i * 8, 0);
          mbar_arrive(SM_KBAR + 16 + i * 8);
          mbar_expect(SM_KBAR + i * 8, KVB);
          bulk_g2s(SM_KV + i * KVS, sc->kv[1] + i * KVB, KVB, SM_KBAR + i * 8);
        }
      }
      bar_sync(2, 512);
#pragma unroll 1
      for (int pass = 0; pass < 2; pass++) {
        float o[12];
        attn_safe(pass, duty, sc->kv[1], d, o);
        finish(pass, o);
      }
    }
  }
}

typedef CUresult (*EncodeFn)(CUtensorMap*, CUtensorMapDataType, cuuint32_t, void*, const cuuint64_t*, const cuuint64_t*,
                             const cuuint32_t*, const cuuint32_t*, CUtensorMapInterleave, CUtensorMapSwizzle,
                             CUtensorMapL2promotion, CUtensorMapFloatOOBfill);

void make_map(EncodeFn fn, CUtensorMap* m, void* p, int rank, int rows, int cols, int box_rows) {
  cuuint64_t dims[3] = {(cuuint64_t)(rank == 2 ? cols : 64), (cuuint64_t)rows, (cuuint64_t)cols / 64};
  cuuint64_t strides[2] = {(cuuint64_t)cols * 2, 128};
  cuuint32_t box[3] = {64, (cuuint32_t)box_rows, 2};
  cuuint32_t es[3] = {1, 1, 1};
  fn(m, CU_TENSOR_MAP_DATA_TYPE_BFLOAT16, rank, p, dims, strides, box, es, CU_TENSOR_MAP_INTERLEAVE_NONE,
     CU_TENSOR_MAP_SWIZZLE_128B, CU_TENSOR_MAP_L2_PROMOTION_L2_128B, CU_TENSOR_MAP_FLOAT_OOB_FILL_NONE);
}

}

extern "C" void kernel_launch(void* const* d_in, const int* in_sizes, int n_in, void* d_out, int out_size) {
  static EncodeFn fn = nullptr;
  static Scratch* sc = nullptr;
  if (!fn) {
    void* p = nullptr;
    cudaDriverEntryPointQueryResult st;
    cudaGetDriverEntryPoint("cuTensorMapEncodeTiled", &p, cudaEnableDefault, &st);
    fn = (EncodeFn)p;
    cudaFuncSetAttribute(fused_kernel, cudaFuncAttributeMaxDynamicSharedMemorySize, SM_TOTAL);
    cudaGetSymbolAddress((void**)&sc, g_scratch);
  }
  Maps maps;
  make_map(fn, &maps.m[0], d_in[0], 3, 2048, 512, 64);
  make_map(fn, &maps.m[1], d_in[1], 3, 512, 512, 64);
  make_map(fn, &maps.m[2], d_in[6], 2, 512, 1792, 64);
  make_map(fn, &maps.m[3], d_in[7], 2, 512, 1792, 64);
  make_map(fn, &maps.m[4], d_in[8], 3, 1792, 512, 64);
  make_map(fn, &maps.m[5], d_in[4], 3, 512, 512, 64);
  make_map(fn, &maps.m[6], d_out, 3, 2048, 512, 16);
  const Descs d{mkdesc(SM_KV, 128, 256, 0), mkdesc(SM_KV + 4096, 128, 2048, 0), mkdesc(SM_X, 16, 1024, 1),
                mkdesc(SM_X, 1024, 128, 0), mkdesc(SM_B, 8192, 1024, 1)};
  fused_kernel<<<128, 640, SM_TOTAL>>>(sc, (const __nv_bfloat16*)d_in[2], (const __nv_bfloat16*)d_in[3],
                                       (const unsigned short*)d_in[9], (const unsigned char*)d_in[0], (const unsigned char*)d_in[1],
                                       (const unsigned char*)d_in[8], (const unsigned char*)d_in[4], 0x9F809F80u, d, maps);
}
```

```cpp
#include <cuda_runtime.h>
#include <cuda_bf16.h>
#include <cuda_fp16.h>
#include <cuda.h>
#include <stdint.h>

namespace {

struct Scratch {
  unsigned int epoch[256];
  unsigned long long kvflag[128];
  unsigned char early[2][16384];
  unsigned int flag[128 * 32];
  unsigned char kv[2][131072];
  unsigned char ex[128 * 8192];
  unsigned char o[128 * 8192];
  unsigned char h[32 * 28 * 8192];
};
__device__ __align__(1024) Scratch g_scratch;
#define TL(i)
#define TLW(i)

struct Maps { CUtensorMap m[6]; };
struct Descs { uint64_t k, v, x, a, b, kk[8], vv[32], xx[32], aa[32], bb[24]; };

constexpr uint32_t KVB = 8192;
constexpr uint32_t KVS = 10240;
constexpr uint32_t SB = 1024;
constexpr uint32_t SM_X = SB;
constexpr uint32_t SM_B = SM_X + 65536;
constexpr uint32_t SM_KV = SM_B + 98304;
constexpr uint32_t SM_Q = SM_KV + 4 * KVS;
constexpr uint32_t SM_A = SM_Q + 16384;
constexpr uint32_t SM_G = SM_A + 8192;
constexpr uint32_t SM_XBAR = SM_G + 256;
constexpr uint32_t SM_BBAR = SM_XBAR + 32;
constexpr uint32_t SM_KBAR = SM_BBAR + 32;
constexpr uint32_t SM_EBAR = SM_KBAR + 32;
constexpr uint32_t SM_OBAR = SM_EBAR + 32;
constexpr uint32_t SM_FBAR = SM_OBAR + 32;
constexpr uint32_t SM_KEBAR = SM_FBAR + 8;
constexpr uint32_t SM_PBAR = SM_KEBAR + 32;
constexpr uint32_t SM_WBAR = SM_PBAR + 8;
constexpr uint32_t SM_SBAR = SM_WBAR + 8;
constexpr uint32_t SM_QBAR = SM_SBAR + 8;
constexpr uint32_t SM_HBAR = SM_QBAR + 8;
constexpr uint32_t SM_KM = SM_HBAR + 8;
static_assert(SM_KM % 16 == 0, "");
constexpr uint32_t SM_MAX = SM_KM + 16;
constexpr uint32_t SM_TL = SM_MAX + 16;
constexpr uint32_t SM_TOTAL = SM_TL - SB;

__device__ __forceinline__ void wg_fence() { asm volatile("wgmma.fence.sync.aligned;" ::: "memory"); }
__device__ __forceinline__ void wg_commit() { asm volatile("wgmma.commit_group.sync.aligned;" ::: "memory"); }
template <int N> __device__ __forceinline__ void wg_wait() { asm volatile("wgmma.wait_group.sync.aligned %0;" ::"n"(N) : "memory"); }
template <int N> __device__ __forceinline__ void regfence(float* d) {
#pragma unroll
  for (int i = 0; i < N; i++) asm volatile("" : "+f"(d[i])::"memory");
}
template <int N> __device__ __forceinline__ void regfence(uint32_t* d) {
#pragma unroll
  for (int i = 0; i < N; i++) asm volatile("" : "+r"(d[i])::"memory");
}
__host__ __device__ constexpr uint64_t mkdesc(uint32_t addr, uint32_t lbo, uint32_t sbo, int sw) {
  return (uint64_t)((addr & 0x3FFFF) >> 4) | ((uint64_t)(lbo >> 4) << 16) | ((uint64_t)(sbo >> 4) << 32) | ((uint64_t)sw << 62);
}
__device__ __forceinline__ void mbar_init(uint32_t a, uint32_t c) { asm volatile("mbarrier.init.shared::cta.b64 [%0], %1;" ::"r"(a), "r"(c) : "memory"); }
__device__ __forceinline__ void mbar_expect(uint32_t a, uint32_t b) { asm volatile("mbarrier.arrive.expect_tx.shared::cta.b64 _, [%0], %1;" ::"r"(a), "r"(b) : "memory"); }
__device__ __forceinline__ bool mbar_try(uint32_t a, uint32_t ph) {
  uint32_t ok;
  asm volatile("{\n.reg .pred p;\nmbarrier.try_wait.parity.shared::cta.b64 p, [%1], %2;\nselp.u32 %0, 1, 0, p;\n}" : "=r"(ok) : "r"(a), "r"(ph) : "memory");
  return ok;
}
__device__ __forceinline__ void mbar_wait(uint32_t a, uint32_t ph) {
  if (mbar_try(a, ph)) return;
#pragma unroll 1
  for (int i = 0; i < (1 << 20); i++)
    if (mbar_try(a, ph)) return;
  __trap();
}
__device__ __forceinline__ void bulk_g2s(uint32_t dst, const void* src, uint32_t bytes, uint32_t mbar) {
  asm volatile("cp.async.bulk.shared::cluster.global.mbarrier::complete_tx::bytes [%0], [%1], %2, [%3];" ::"r"(dst), "l"(src), "r"(bytes), "r"(mbar) : "memory");
}
__device__ __forceinline__ void tma_load(uint32_t dst, const CUtensorMap* m, int x, int y, uint32_t mbar) {
  asm volatile("cp.async.bulk.tensor.2d.shared::cluster.global.mbarrier::complete_tx::bytes [%0], [%1, {%2, %3}], [%4];" ::"r"(dst), "l"(m), "r"(x), "r"(y), "r"(mbar) : "memory");
}
__device__ __forceinline__ void tma_load3(uint32_t dst, const CUtensorMap* m, int y, int z, uint32_t mbar) {
  asm volatile("cp.async.bulk.tensor.3d.shared::cluster.global.mbarrier::complete_tx::bytes [%0], [%1, {0, %2, %3}], [%4];" ::"r"(dst), "l"(m), "r"(y), "r"(z), "r"(mbar) : "memory");
}
__device__ __forceinline__ void tma_prefetch(const CUtensorMap* m, int x, int y) {
  asm volatile("cp.async.bulk.prefetch.tensor.2d.L2.global.tile [%0, {%1, %2}];" ::"l"(m), "r"(x), "r"(y) : "memory");
}
__device__ __forceinline__ void l2_prefetch(const void* p, uint32_t bytes) {
  asm volatile("cp.async.bulk.prefetch.L2.global [%0], %1;" ::"l"(p), "r"(bytes) : "memory");
}
__device__ __forceinline__ void fence_async() { asm volatile("fence.proxy.async.global;" ::: "memory"); }
__device__ __forceinline__ void fence_async_smem() { asm volatile("fence.proxy.async.shared::cta;" ::: "memory"); }
__device__ __forceinline__ void fence_acquire() { asm volatile("fence.acquire.gpu;" ::: "memory"); }
__device__ __forceinline__ bool elect() {
  uint32_t r;
  asm volatile("{\n.reg .pred p;\nelect.sync _|p, 0xffffffff;\nselp.u32 %0, 1, 0, p;\n}" : "=r"(r));
  return r;
}
__device__ __forceinline__ void mbar_arrive(uint32_t a) { asm volatile("mbarrier.arrive.shared::cta.b64 _, [%0];" ::"r"(a) : "memory"); }
__device__ __forceinline__ void bar_sync(int id, int n) { asm volatile("bar.sync %0, %1;" ::"r"(id), "r"(n) : "memory"); }
__device__ __forceinline__ void bar_arrive(int id, int n) { asm volatile("bar.arrive %0, %1;" ::"r"(id), "r"(n) : "memory"); }
__device__ __forceinline__ void red_max_s(uint32_t a, uint32_t v) { asm volatile("red.shared::cta.max.u32 [%0], %1;" ::"r"(a), "r"(v) : "memory"); }
__device__ __forceinline__ uint32_t lds32(uint32_t a) { uint32_t r; asm volatile("ld.shared.u32 %0, [%1];" : "=r"(r) : "r"(a) : "memory"); return r; }
__device__ __forceinline__ float ldsf(uint32_t a) { return __uint_as_float(lds32(a)); }
__device__ __forceinline__ void sts32(uint32_t a, uint32_t v) { asm volatile("st.shared.u32 [%0], %1;" ::"r"(a), "r"(v) : "memory"); }
__device__ __forceinline__ uint4 lds128(uint32_t a) {
  uint4 r;
  asm volatile("ld.shared.v4.u32 {%0,%1,%2,%3}, [%4];" : "=r"(r.x), "=r"(r.y), "=r"(r.z), "=r"(r.w) : "r"(a) : "memory");
  return r;
}
__device__ __forceinline__ void sts128(uint32_t a, uint4 v) { asm volatile("st.shared.v4.u32 [%0], {%1,%2,%3,%4};" ::"r"(a), "r"(v.x), "r"(v.y), "r"(v.z), "r"(v.w) : "memory"); }
__device__ __forceinline__ uint32_t pack_bf16(float lo, float hi) { uint32_t r; asm("cvt.rn.bf16x2.f32 %0, %1, %2;" : "=r"(r) : "f"(hi), "f"(lo)); return r; }
__device__ __forceinline__ uint32_t pack_f16(float lo, float hi) { uint32_t r; asm("cvt.rn.f16x2.f32 %0, %1, %2;" : "=r"(r) : "f"(hi), "f"(lo)); return r; }
__device__ __forceinline__ float bf_lo(uint32_t v) { return __uint_as_float(v << 16); }
__device__ __forceinline__ float bf_hi(uint32_t v) { return __uint_as_float(v & 0xFFFF0000u); }
__device__ __forceinline__ float ex2(float a) { float x; asm("ex2.approx.ftz.f32 %0, %1;" : "=f"(x) : "f"(a)); return x; }
__device__ __forceinline__ uint32_t ld_relaxed(const unsigned int* p) {
  uint32_t v;
  asm volatile("ld.relaxed.gpu.global.u32 %0, [%1];" : "=r"(v) : "l"(p) : "memory");
  return v;
}
__device__ __forceinline__ uint4 ld_relaxed4(const void* p) {
  uint4 v;
  asm volatile("ld.relaxed.gpu.global.v4.u32 {%0,%1,%2,%3}, [%4];" : "=r"(v.x), "=r"(v.y), "=r"(v.z), "=r"(v.w) : "l"(p) : "memory");
  return v;
}
__device__ __forceinline__ void st_relaxed4(void* p, uint32_t x, uint32_t y, uint32_t z, uint32_t w) {
  asm volatile("st.relaxed.gpu.global.v4.u32 [%0], {%1,%2,%3,%4};" ::"l"(p), "r"(x), "r"(y), "r"(z), "r"(w) : "memory");
}
__device__ __forceinline__ void wait_flag(const unsigned int* p, uint32_t v, uint32_t target) {
#pragma unroll 1
  for (int i = 0; i < (1 << 21) && (int)(v - target) < 0; i++) v = ld_relaxed(p);
  if ((int)(v - target) < 0) __trap();
  fence_acquire();
  fence_async();
}
__device__ __forceinline__ void stsm4(uint32_t a, uint32_t r0, uint32_t r1, uint32_t r2, uint32_t r3) {
  asm volatile("stmatrix.sync.aligned.m8n8.x4.shared.b16 [%0], {%1,%2,%3,%4};" ::"r"(a), "r"(r0), "r"(r1), "r"(r2), "r"(r3) : "memory");
}

#define R4(d, i) "+f"(d[i]), "+f"(d[i + 1]), "+f"(d[i + 2]), "+f"(d[i + 3])
#define R8(d, i) R4(d, i), R4(d, i + 4)
#define R32(d, i) R8(d, i), R8(d, i + 8), R8(d, i + 16), R8(d, i + 24)
#define L4 "%0,%1,%2,%3"
#define L8 L4 ",%4,%5,%6,%7"
#define L12 L8 ",%8,%9,%10,%11"
#define L32 L12 ",%12,%13,%14,%15,%16,%17,%18,%19,%20,%21,%22,%23,%24,%25,%26,%27,%28,%29,%30,%31"
#define L64 L32 ",%32,%33,%34,%35,%36,%37,%38,%39,%40,%41,%42,%43,%44,%45,%46,%47,%48,%49,%50,%51,%52,%53,%54,%55,%56,%57,%58,%59,%60,%61,%62,%63"
__device__ __forceinline__ void mma_ss128(float* d, uint64_t da, uint64_t db, int sd) {
  asm volatile("{\n.reg .pred p;\nsetp.ne.b32 p, %66, 0;\nwgmma.mma_async.sync.aligned.m64n128k16.f32.bf16.bf16 {" L64 "}, %64, %65, p, 1, 1, 0, 1;\n}\n"
               : R32(d, 0), R32(d, 32) : "l"(da), "l"(db), "r"(sd));
}
__device__ __forceinline__ void mma_ss24(float* d, uint64_t da, uint64_t db) {
  asm volatile("wgmma.mma_async.sync.aligned.m64n24k16.f32.bf16.bf16 {" L12 "}, %12, %13, 1, 1, 1, 0, 1;\n" : R8(d, 0), R4(d, 8) : "l"(da), "l"(db));
}
__device__ __forceinline__ void mma_qk_f16(float* d, const uint32_t* a, uint64_t db) {
  asm volatile("wgmma.mma_async.sync.aligned.m64n64k16.f32.f16.f16 {" L32 "}, {%32,%33,%34,%35}, %36, 1, 1, 1, 0;\n"
               : R32(d, 0) : "r"(a[0]), "r"(a[1]), "r"(a[2]), "r"(a[3]), "l"(db));
}
__device__ __forceinline__ void mma_qk_bf16(float* d, const uint32_t* a, uint64_t db) {
  asm volatile("wgmma.mma_async.sync.aligned.m64n64k16.f32.bf16.bf16 {" L32 "}, {%32,%33,%34,%35}, %36, 0, 1, 1, 0;\n"
               : R32(d, 0) : "r"(a[0]), "r"(a[1]), "r"(a[2]), "r"(a[3]), "l"(db));
}
__device__ __forceinline__ void mma_pv(float* d, const uint32_t* a, uint64_t db) {
  asm volatile("wgmma.mma_async.sync.aligned.m64n24k16.f32.bf16.bf16 {" L12 "}, {%12,%13,%14,%15}, %16, 1, 1, 1, 1;\n"
               : R8(d, 0), R4(d, 8) : "r"(a[0]), "r"(a[1]), "r"(a[2]), "r"(a[3]), "l"(db));
}

__device__ __forceinline__ uint32_t exp_mufu(float a, float b) { return pack_bf16(ex2(a), ex2(b)); }
constexpr float EXP_MAGIC = 446.0f + 0.00390625f - 0.5860f;
#define PM 0xAAAAu
#define NX 8
#define KP 4
#define KU 5
#define QP 1
#define OT 24
#define VB 1
#define DT 2
#define CP 1
#define QA 1
#define CR 1
#define LB 1
#define FB 1
#define TB 1
#define ORD 0x2013
#define JX 14
__host__ __device__ constexpr uint32_t poly_mask(int h) { return PM | (h < NX ? 1u << JX : 0u); }
__device__ __forceinline__ uint32_t exp_soft(float t0, float t1, uint32_t cor) {
  uint32_t y = __byte_perm(__float_as_uint(t0), __float_as_uint(t1), 0x6521);
  uint32_t u, r;
  asm("lop3.b32 %0, %1, 0x007F007F, %2, 0xEA;" : "=r"(u) : "r"(y), "r"(cor));
  uint32_t e = y - u;
  asm("fma.rn.bf16x2 %0, %1, %2, %3;" : "=r"(r) : "r"(y), "r"(u), "r"(e));
  return r;
}
constexpr float QSCALE = 0.25f * 1.4426950408889634f;

__host__ __device__ constexpr uint32_t off_k(int h) { return ((h >> 1) * KVS + (h & 1) * 2048) >> 4; }
__host__ __device__ constexpr uint32_t off_v(int h) { return ((h >> 1) * KVS + (h & 1) * 1024) >> 4; }

__device__ __forceinline__ void kv_advance(int sl, int it, int duty, const unsigned char* src) {
  if ((threadIdx.x & 31) == 0) mbar_arrive(SM_KEBAR + ((sl + 3) & 3) * 8);
  if (duty == sl) {
    const int t = (sl + 2) & 3;
    mbar_wait(SM_KEBAR + t * 8, (sl == 0 ? it + 1 : it) & 1);
    if (elect()) {
      mbar_expect(SM_KBAR + t * 8, KVB);
      bulk_g2s(SM_KV + t * KVS, src + ((4 * it + sl + 2) & 15) * KVB, KVB, SM_KBAR + t * 8);
    }
  }
}

#define SIGM 3
__device__ __forceinline__ void publish(int pass, int it, int duty, unsigned int* flag) {
  if (pass == 1 && (SIGM == 3 ? it == 6 - 2 * duty : SIGM == 1 ? it == 0 && duty == 3 : it == 2 && duty == 3)) {
    mbar_wait(it ? SM_FBAR : SM_HBAR, 0);
    if (it) mbar_wait(SM_PBAR, 0);
    if (elect()) asm volatile("st.release.gpu.global.u32 [%0], %1;" ::"l"(flag), "r"(2 * lds32(SM_MAX + 4) - 1 + (it >> 1)) : "memory");
  }
}

__device__ __forceinline__ void attn_fast(int pass, int duty0, const unsigned char* src, unsigned int* flag, uint32_t cor, const Descs& d, uint4 v, float* o) {
  uint32_t q[4], p[16];
  float s[32];
  {
    int tid = threadIdx.x;
    if (OT & 2) asm volatile("mov.u32 %0, %%tid.x;" : "=r"(tid));
    if (!QP) v = lds128(SM_Q + pass * 8192 + tid * 16);
    q[0] = v.x, q[1] = v.y, q[2] = v.z, q[3] = v.w;
#pragma unroll
    for (int i = 0; i < 4; i++) q[i] = pack_f16(bf_lo(q[i]) * QSCALE, bf_hi(q[i]) * QSCALE);
  }
#pragma unroll
  for (int i = 0; i < 12; i++) o[i] = 0.f;
#pragma unroll
  for (int j = 0; j < 32; j++) s[j] = ((poly_mask(0) >> (j / 2)) & 1) ? EXP_MAGIC : 0.f;
  regfence<12>(o); regfence<32>(s); regfence<4>(q);
  __syncwarp();
  if (pass == 1 && (threadIdx.x & 31) == 0) mbar_arrive(SM_PBAR);
  if (!VB || LB) mbar_wait(SM_SBAR, 0);
  if (LB) {
    if (pass == 0 && (threadIdx.x >> 7) == 2) { TL(53); }
    wg_fence();
    mma_qk_f16(s, q, d.k);
    wg_commit();
  }
#pragma unroll 1
  for (int it = 0; it < 4; it++) {
    const int duty = pass + it == (duty0 & 2) * 2 ? -1 : duty0;
    publish(pass, it, duty, flag);
    if (!LB) {
      mbar_wait(VB && pass + it == 0 ? SM_SBAR : SM_KBAR, it & 1);
      if (pass + it == 0 && (threadIdx.x >> 7) == 2) { TL(53); }
      wg_fence();
      mma_qk_f16(s, q, d.k);
      wg_commit();
    }
#pragma unroll
    for (int h = 0; h < 8; h++) {
      wg_wait<0>();
      regfence<32>(s);
      if ((h & 1) == 0) kv_advance(h >> 1, it, duty, src);
#pragma unroll
      for (int j = 0; j < 16; j++)
        p[j] = ((poly_mask(h) >> j) & 1) ? exp_soft(s[2 * j], s[2 * j + 1], cor) : exp_mufu(s[2 * j], s[2 * j + 1]);
#pragma unroll
      for (int j = 0; j < 32; j++) {
        const int a = (poly_mask(h) >> (j / 2)) & 1, b = (poly_mask((h + 1) & 7) >> (j / 2)) & 1;
        if (a != b) asm volatile("add.f32 %0, %0, %2;" : "+f"(s[j]), "+r"(p[j / 2]) : "f"(a ? -EXP_MAGIC : EXP_MAGIC) : "memory");
      }
      if (h < 7 && (h & 1)) mbar_wait(SM_KBAR + ((h + 1) >> 1) * 8, it & 1);
      if (LB && h == 7) mbar_wait(pass + it == 4 ? SM_SBAR : SM_KBAR, ~it & 1);
      wg_fence();
#pragma unroll
      for (int i = 0; i < 4; i++) mma_pv(o, p + 4 * i, (DT & 2) ? d.vv[4 * h + i] : d.v + off_v(h) + i * 16);
      if (h < 7 || LB) mma_qk_f16(s, q, (DT & 1) ? d.kk[(h + 1) & 7] : d.k + off_k((h + 1) & 7));
      wg_commit();
    }
  }
  wg_wait<0>();
  regfence<12>(o); regfence<32>(s);
}

__device__ __forceinline__ void attn_safe(int pass, int duty, const unsigned char* src, unsigned int* flag, const Descs& d, float* o) {
  uint32_t q[4], p[16];
  float s[32];
  float m0 = -INFINITY, m1 = -INFINITY;
  {
    const uint4 v = lds128(SM_Q + pass * 8192 + threadIdx.x * 16);
    q[0] = v.x, q[1] = v.y, q[2] = v.z, q[3] = v.w;
  }
#pragma unroll
  for (int i = 0; i < 12; i++) o[i] = 0.f;
#pragma unroll
  for (int j = 0; j < 32; j++) s[j] = 0.f;
  regfence<12>(o); regfence<32>(s); regfence<4>(q);
  __syncwarp();
  if (pass == 1 && (threadIdx.x & 31) == 0) mbar_arrive(SM_PBAR);
#pragma unroll 1
  for (int i = 0; i < 32; i++) {
    const int h = i & 7, it = i >> 3;
    if (pass + it == 4 && duty >= 2) duty = -1;
    if (h == 0) publish(pass, it, duty, flag);
    mbar_wait(SM_KBAR + (h >> 1) * 8, ~it & 1);
    wg_fence();
    mma_qk_bf16(s, q, d.k + off_k(h));
    wg_commit();
    wg_wait<0>();
    regfence<32>(s); regfence<12>(o);
    if ((h & 1) == 0) kv_advance(h >> 1, it, duty, src);
    float n0 = m0, n1 = m1;
#pragma unroll
    for (int j = 0; j < 16; j++) {
      const uint32_t r = pack_bf16(s[2 * j], s[2 * j + 1]);
      s[2 * j] = bf_lo(r), s[2 * j + 1] = bf_hi(r);
      if (j & 1) n1 = fmaxf(n1, fmaxf(s[2 * j], s[2 * j + 1])); else n0 = fmaxf(n0, fmaxf(s[2 * j], s[2 * j + 1]));
    }
    n0 = fmaxf(n0, __shfl_xor_sync(~0u, n0, 1)); n0 = fmaxf(n0, __shfl_xor_sync(~0u, n0, 2));
    n1 = fmaxf(n1, __shfl_xor_sync(~0u, n1, 1)); n1 = fmaxf(n1, __shfl_xor_sync(~0u, n1, 2));
    const float a0 = ex2((m0 - n0) * QSCALE), a1 = ex2((m1 - n1) * QSCALE);
    m0 = n0, m1 = n1;
#pragma unroll
    for (int j = 0; j < 12; j++) o[j] *= (j & 2) ? a1 : a0;
#pragma unroll
    for (int j = 0; j < 16; j++) {
      const float m = (j & 1) ? m1 : m0;
      p[j] = exp_mufu((s[2 * j] - m) * QSCALE, (s[2 * j + 1] - m) * QSCALE);
    }
    regfence<12>(o);
    wg_fence();
#pragma unroll
    for (int j = 0; j < 4; j++) mma_pv(o, p + 4 * j, d.v + off_v(h) + j * 16);
    wg_commit();
  }
  wg_wait<0>();
  regfence<12>(o); regfence<32>(s);
}

__global__ void __launch_bounds__(640, 1)
fused_kernel(Scratch* __restrict__ sc, const __nv_bfloat16* __restrict__ wk, const __nv_bfloat16* __restrict__ wv,
             const unsigned short* __restrict__ gw, const unsigned char* __restrict__ pf_x, const unsigned char* __restrict__ pf_wq,
             const unsigned char* __restrict__ pf_down, const unsigned char* __restrict__ pf_wo, uint4* __restrict__ out, uint32_t cor,
             const __grid_constant__ Descs d, const __grid_constant__ Maps maps) {
  extern __shared__ __align__(1024) unsigned char smem[];
  const int tid = threadIdx.x, wid = __shfl_sync(~0u, tid >> 5, 0), wg = wid >> 2, warp = wid & 3, lane = tid & 31;
  const int bid = blockIdx.x, c = bid & 3, T = bid >> 2;
  if (tid == 0) { TLW(63); }

  uint4 wv0, wv1;
  unsigned short gv = 0;
  uint32_t ep = 0;
  if (tid < 512) {
    if (c < 2) wv0 = __ldg((const uint4*)(c == 0 ? wk : wv) + tid), wv1 = __ldg((const uint4*)(c == 0 ? wk : wv) + 512 + tid);
    gv = __ldg(gw + tid);
    if (wid < 4 || wid == 12) ep = ld_relaxed(sc->epoch + bid);
  }
  if (wid == 16) {
    if (elect()) {
      l2_prefetch(pf_x + bid * 16384, 16384);
#pragma unroll
      for (int i = 0; i < 8; i++) mbar_init(SM_XBAR + 8 * i, 1);
      asm volatile("fence.mbarrier_init.release.cluster;" ::: "memory");
#pragma unroll
      for (int i = 0; i < 4; i++) {
        mbar_expect(SM_XBAR + 8 * i, 16384);
        tma_load3(SM_X + i * 16384, &maps.m[0], 64 * T, 2 * i, SM_XBAR + 8 * i);
      }
      l2_prefetch(pf_wq + bid * 4096, 4096);
#pragma unroll
      for (int i = 0; i < 4; i++) {
        mbar_expect(SM_BBAR + 8 * i, 16384);
        tma_load3(SM_B + i * 16384, &maps.m[1], 64 * i, 2 * c, SM_BBAR + 8 * i);
      }
    }
    __syncwarp();
    TLW(29);
  }
  if (wid == 17) {
    if (elect()) {
#pragma unroll
      for (int i = 8; i < 30; i++) mbar_init(SM_XBAR + 8 * i, i < 12 || i == 26 ? 1 : i < 21 || i >= 28 ? 4 : i == 27 ? 12 : 16);
#pragma unroll
      for (int i = 0; i < 2; i++) mbar_arrive(SM_KBAR + 8 * i);
      sts32(SM_MAX, 0);
      asm volatile("fence.mbarrier_init.release.cluster;" ::: "memory");
#pragma unroll
      for (int i = 2; i < 6; i++) asm volatile("prefetch.tensormap [%0];" ::"l"(&maps.m[i]) : "memory");
      if ((uint32_t)__cvta_generic_to_shared(smem) != SB) __trap();
    }
    __syncwarp();
  }
  TL(32 + wg);
  if (tid < 512) {
    sts128(SM_KV + wg * KVS + KVB + (tid & 127) * 16, make_uint4(0x3F80u, 0, 0, 0));
    if (c < 2) {
      sts128(SM_KV + KVS + (tid & 1) * KVS + (tid >> 1) * 16, wv0);
      sts128(SM_KV + KVS + (tid & 1) * KVS + (tid >> 1) * 16 + 4096, wv1);
    }
    asm volatile("st.shared.u16 [%0], %1;" ::"r"(SM_KV + 3 * KVS + tid * 16), "h"(gv) : "memory");
    TL(37 + wg);
    fence_async_smem();
  }
  TL(42 + wg);
  if (wg == 4) { TLW(46 + warp); }
  bar_sync(0, 640);

  if (wg == 4) {
    float acc[64];
    auto stage = [&](int sl, uint32_t ph, const uint64_t* da, bool first) {
      mbar_wait(SM_BBAR + sl * 8, ph);
      wg_fence();
      mma_ss128(acc, da[0], d.bb[4 * sl], !first);
#pragma unroll
      for (int k = 1; k < 4; k++) mma_ss128(acc, da[k], d.bb[4 * sl + k], 1);
      wg_commit();
    };
    auto release = [&](int sl, uint32_t ph) {
      if (lane == 0) mbar_arrive(SM_EBAR + sl * 8);
      if (warp != sl) return false;
      mbar_wait(SM_EBAR + sl * 8, ph);
      return true;
    };
    const uint32_t bbar = SM_BBAR + warp * 8, bdst = SM_B + warp * 16384;
    auto load_w = [&](int m, int y) {
      if (elect()) {
        mbar_expect(bbar, 16384);
        tma_load3(bdst, &maps.m[m], y, 2 * c, bbar);
      }
    };
    auto load_gu = [&](int x, int y) {
      if (elect()) {
        mbar_expect(bbar, 16384);
        tma_load(bdst, &maps.m[2], x, y, bbar);
        tma_load(bdst + 8192, &maps.m[3], x, y, bbar);
      }
    };
    auto load_aw = [&](const unsigned char* a, int m, int y) {
      if (elect()) {
        mbar_expect(bbar, 24576);
        bulk_g2s(SM_X + warp * 8192, a, 8192, bbar);
        tma_load3(bdst, &maps.m[m], y, 2 * c, bbar);
      }
    };
    auto signal = [&](uint32_t v) {
      if (elect()) asm volatile("st.release.gpu.global.u32 [%0], %1;" ::"l"(sc->flag + bid * 32), "r"(v) : "memory");
    };
    const unsigned int* pflag = sc->flag + (T * 4 + warp) * 32;
    const unsigned char* hsrc = sc->h + (T * 4 + warp) * 7 * 8192;
    uint32_t fv = 0;
    if (c < 2) bar_sync(7, 256);
#pragma unroll
    for (int kb = 0; kb < 9; kb++) {
      if (kb < 8) {
        if ((kb & 1) == 0) mbar_wait(SM_XBAR + kb * 4, 0);
        if (QA) {
          mbar_wait(SM_BBAR + (kb & 3) * 8, kb >> 2);
          wg_fence();
#pragma unroll
          for (int k = 0; k < 4; k++) mma_ss128(acc, d.x + kb * 512 + k * 2, d.b + (kb & 3) * 1024 + k * 128, kb + k > 0);
          wg_commit();
        } else {
          stage(kb & 3, kb >> 2, d.xx + kb * 4, kb == 0);
        }
      }
      if (kb > 0) {
        if (kb < 8) wg_wait<1>(); else wg_wait<0>();
        if (release((kb - 1) & 3, (kb - 1) >> 2)) {
          if (kb < 5) load_w(1, (kb + 3) * 64);
          else load_gu(448 * c, warp * 64);
        }
      }
    }
    regfence<64>(acc);
    {
      uint32_t q[32], m = 0;
#pragma unroll
      for (int j = 0; j < 32; j++) q[j] = pack_bf16(acc[2 * j], acc[2 * j + 1]);
#pragma unroll
      for (int h = 0; h < 8; h++) sts128(SM_Q + h * 2048 + (tid - 512) * 16, make_uint4(q[4 * h], q[4 * h + 1], q[4 * h + 2], q[4 * h + 3]));
      __syncwarp();
      if (lane == 0) mbar_arrive(SM_QBAR);
      TL(12);
#pragma unroll
      for (int j = 0; j < 16; j++) {
        const uint32_t* a = q + (j >> 1) * 4;
        float g[4];
        asm("mma.sync.aligned.m16n8k16.row.col.f32.bf16.bf16.f32 {%0,%1,%2,%3}, {%4,%5,%6,%7}, {%8,%9}, {%10,%10,%10,%10};"
            : "=f"(g[0]), "=f"(g[1]), "=f"(g[2]), "=f"(g[3])
            : "r"(a[0]), "r"(a[1]), "r"(a[2]), "r"(a[3]), "r"(a[j & 1]), "r"(a[2 + (j & 1)]), "f"(0.f));
        m = max((int)m, max(__float_as_int(g[(j & 1) * 2]), __float_as_int(g[(j & 1) * 2 + 1])));
      }
      m = __reduce_max_sync(~0u, m);
      if (lane == 0) red_max_s(SM_MAX, m);
    }
    const uint32_t epoch = ld_relaxed(sc->epoch + bid) + 1;
#pragma unroll 1
    for (int u = 0; u < 7; u++) {
      const int x = 448 * c + 64 * u;
#pragma unroll
      for (int kb = 0; kb < 9; kb++) {
        if (kb < 8) stage(kb & 3, kb >> 2, d.xx + kb * 4, kb == 0);
        if (kb > 0) {
          if (kb < 8) wg_wait<1>(); else wg_wait<0>();
          if (kb == KP && u == 0 && warp == KU - 5) fv = ld_relaxed((const unsigned int*)sc->kvflag);
          if (release((kb - 1) & 3, (kb - 1) >> 2)) {
            if (kb < 5) {
              load_gu(x, (kb + 3) * 64);
              if (!(SIGM & 1) && kb == 1 && u == 5) signal(2 * epoch - 1);
              if (u == 6) fv = ld_relaxed(pflag);
            } else if (u < 6) {
              load_gu(x + 64, (kb - 5) * 64);
              if (kb == KU && u == 0) {
                TLW(56);
                wait_flag((const unsigned int*)sc->kvflag, fv, epoch << 8);
                mbar_wait(SM_SBAR, 0);
                if (elect()) {
                  mbar_expect(SM_KBAR + 16, KVB + 16);
                  bulk_g2s(SM_KV + 2 * KVS, sc->kv[0] + 2 * KVB, KVB, SM_KBAR + 16);
                  bulk_g2s(SM_KM, sc->kvflag, 16, SM_KBAR + 16);
                  mbar_expect(SM_KBAR + 24, KVB);
                  bulk_g2s(SM_KV + 3 * KVS, sc->kv[0] + 3 * KVB, KVB, SM_KBAR + 24);
                }
                TLW(51);
              }
            } else {
              wait_flag(pflag, fv, 2 * epoch - 1);
              load_aw(hsrc, 4, warp * 448);
            }
          }
        }
      }
      regfence<64>(acc);
      uint32_t* hp = (uint32_t*)(sc->h + (bid * 7 + u) * 8192 + warp * 256) + lane;
#pragma unroll
      for (int j = 0; j < 16; j++) {
        float h[2];
#pragma unroll
        for (int e = 0; e < 2; e++) {
          const float x = acc[2 * j + e];
          float t;
          asm("tanh.approx.f32 %0, %1;" : "=f"(t) : "f"(x * fmaf(x * x, 0.044715f * 0.7978845608028654f, 0.7978845608028654f)));
          const float w = x * acc[32 + 2 * j + e];
          h[e] = fmaf(w, t, w);
        }
        hp[(j >> 1) * 256 + (j & 1) * 32] = pack_bf16(h[0], h[1]);
      }
      if (u == 0) {
#pragma unroll
        for (int i = 0; i < 4; i++) *(uint4*)(sc->ex + bid * 8192 + i * 2048 + (tid - 512) * 16) = make_uint4(~0u, ~0u, ~0u, ~0u);
        if (warp == 3 && elect()) {
          l2_prefetch(pf_down + bid * 14336, 14336);
          l2_prefetch(pf_wo + bid * 4096, 4096);
        }
      }
      __syncwarp();
      if ((SIGM & 1) && u == 4 && lane == 0) mbar_arrive(SM_HBAR);
      TL(13 + u);
    }
    if (lane == 0) mbar_arrive(SM_FBAR);
    if (warp == 2 && elect()) {
      mbar_expect(SM_WBAR, 32768);
      tma_load3(SM_B + 65536, &maps.m[5], 320, 2 * c, SM_WBAR);
      tma_load3(SM_B + 81920, &maps.m[5], 448, 2 * c, SM_WBAR);
    }
    const unsigned char* osrc = sc->o + (T * 4 + warp) * 8192;
#pragma unroll 1
    for (int g = 0; g < 7; g++) {
#pragma unroll
      for (int j = 0; j < 4; j++) {
        stage(j, g & 1, d.aa + j * 4, g == 0 && j == 0);
        wg_wait<1>();
        const int n = j == 0 ? g : g + 1;
        if ((j > 0 || g > 0) && release((j + 3) & 3, (n + 1) & 1)) {
          if (n == 5) wait_flag(pflag, fv, 2 * epoch);
          if (FB & 1) load_aw(n < 7 ? hsrc + n * 8192 : osrc, n < 7 ? 4 : 5, n < 7 ? warp * 448 + n * 64 : warp * 128);
          else if (n < 7) load_aw(hsrc + n * 8192, 4, warp * 448 + n * 64); else load_aw(osrc, 5, warp * 128);
          if (n == 4) fv = ld_relaxed(pflag);
          if (j == 0 && n == 5) {
            mbar_wait(SM_PBAR, 0);
            if (elect()) {
              mbar_expect(SM_XBAR, 24576);
              bulk_g2s(SM_A, osrc, 8192, SM_XBAR);
              tma_load3(SM_Q, &maps.m[5], 384, 2 * c, SM_XBAR);
            }
          }
          if (!(SIGM & 2) && j == 1 && n == 2) {
            mbar_wait(SM_PBAR, 0);
            signal(2 * epoch);
          }
        }
      }
    }
    wg_wait<0>();
    if (release(3, 0)) load_w(5, 64);
    regfence<64>(acc);
    TL(20);
    {
      const uint32_t ad = SM_G + (warp * 16 + (lane >> 2)) * 4;
      const float s0 = 0.5f - 0.5f * ldsf(ad), s1 = 0.5f - 0.5f * ldsf(ad + 32);
#pragma unroll
      for (int j = 0; j < 64; j++) acc[j] *= (j & 2) ? s1 : s0;
      regfence<64>(acc);
    }
    mbar_wait(SM_XBAR, 1);
    wg_fence();
#pragma unroll
    for (int k = 0; k < 4; k++) mma_ss128(acc, d.a + ((SM_A - SM_X) >> 4) + k * 128, d.b + ((SM_Q - SM_B) >> 4) + k * 128, 1);
    wg_commit();
#pragma unroll
    for (int j = 0; j < 3; j++) {
      stage(j, 1, d.aa + j * 4, false);
      if (j == 0) {
        wg_wait<1>();
        if (release(0, 1) && elect()) {
          mbar_expect(SM_XBAR + 8, 16384);
          tma_load3(SM_Q, &maps.m[5], 192, 2 * c, SM_XBAR + 8);
        }
      }
    }
    TL(21);
    mbar_wait(SM_WBAR, 0);
    mbar_wait(SM_BBAR + 24, 1);
    mbar_wait(SM_XBAR + 8, 1);
    if (tid == 512) sc->epoch[bid] = epoch;
    TL(22);
#pragma unroll
    for (int i = 0; i < 4; i++) {
      const int w = (ORD >> (4 * i)) & 3;
      mbar_wait(SM_OBAR + w * 8, 0);
      wg_fence();
#pragma unroll
      for (int j = 0; j < 4; j++) mma_ss128(acc, d.aa[16 + 4 * j + w], j == 1 ? d.b + ((SM_Q - SM_B) >> 4) + w * 128 : d.bb[(j == 0 ? 12 : 4 * j + 8) + w], 1);
      wg_commit();
    }
    TL(23);
    wg_wait<0>();
    regfence<64>(acc);
    if (!TB) bar_sync(1, 128);
    TL(24);
    {
      const int r = (lane & 7) + (lane & 8);
      const uint32_t wb = (TB ? SM_KV : SM_Q) + warp * 4096;
#pragma unroll
      for (int j = 0; j < 8; j++) {
        const int blk = 2 * j + (lane >> 4);
        stsm4(wb + (blk >> 3) * 2048 + r * 128 + (((blk & 7) ^ (r & 7)) << 4),
              pack_bf16(acc[8 * j], acc[8 * j + 1]), pack_bf16(acc[8 * j + 2], acc[8 * j + 3]),
              pack_bf16(acc[8 * j + 4], acc[8 * j + 5]), pack_bf16(acc[8 * j + 6], acc[8 * j + 7]));
      }
      __syncwarp();
      uint4* op = out + (64 * T + 16 * warp + (lane >> 4)) * 64 + c * 16 + (lane & 15);
#pragma unroll
      for (int i = 0; i < 8; i++) {
        const int row = 2 * i + (lane >> 4);
        op[i * 128] = lds128(wb + (lane & 8) * 256 + row * 128 + (((lane & 7) ^ (row & 7)) << 4));
      }
    }
    TL(25);
  } else {
    uint4 qv = make_uint4(0, 0, 0, 0);
    if (wg == 0) {
      TL(31);
      float a[12];
#pragma unroll
      for (int i = 0; i < 12; i++) a[i] = 0.f;
      constexpr uint64_t dw = mkdesc(SM_KV + KVS, 128, KVS, 0);
      regfence<12>(a);
#pragma unroll
      for (int kb = 0; kb < 4; kb++) {
        mbar_wait(SM_XBAR + kb * 8, 0);
        if (kb == 0) { TL(27); }
        if (kb == 3) { TL(28); }
        wg_fence();
#pragma unroll
        for (int k = 0; k < 8; k++) mma_ss24(a, d.x + kb * 1024 + (k >> 2) * 512 + (k & 3) * 2, dw + (kb * 8 + k) * 16);
        wg_commit();
      }
      wg_wait<0>();
      regfence<12>(a);
      TL(0);
      if (c < 2) {
        bar_arrive(7, 256);
        const uint32_t ad = SM_KV + (warp * 16 + (lane >> 2)) * 32 + (lane & 3) * 4;
        sts32(ad, pack_bf16(a[0], a[1]));
        sts32(ad + 256, pack_bf16(a[2], a[3]));
        sts32(ad + 16, pack_bf16(a[4], a[5]));
        sts32(ad + 272, pack_bf16(a[6], a[7]));
        bar_sync(6, 128);
        TL(54);
        const int r = tid >> 1, hb = tid & 1, j = r >> 1, kk = (j & 1) * 64 + 2 * T + (r & 1);
        const uint4 v = lds128(SM_KV + tid * 16);
        uint4 e = v;
        int off = (j >> 1) * KVB + 4096 + hb * 2048 + kk * 16;
        if (c == 0) {
          uint4 w = make_uint4(0, 0, 0, 0);
          if (r >= 2) w = lds128(SM_KV + tid * 16 - 64);
          e.x = pack_f16(bf_lo(v.x) - bf_lo(w.x), bf_hi(v.x) - bf_hi(w.x));
          e.y = pack_f16(bf_lo(v.y) - bf_lo(w.y), bf_hi(v.y) - bf_hi(w.y));
          e.z = pack_f16(bf_lo(v.z) - bf_lo(w.z), bf_hi(v.z) - bf_hi(w.z));
          e.w = pack_f16(bf_lo(v.w) - bf_lo(w.w), bf_hi(v.w) - bf_hi(w.w));
          off = (j >> 1) * KVB + (kk >> 3) * 256 + hb * 128 + (kk & 7) * 16;
        }
        if (tid < 16) st_relaxed4(sc->early[ep & 1] + off, ~e.x, ~e.y, ~e.z, ~e.w);
        if (tid == 0) asm volatile("red.relaxed.gpu.global.add.u64 [%0], 4;" ::"l"(sc->kvflag + 16) : "memory");
        bar_arrive(3, 512);
        *(uint4*)(sc->kv[0] + off) = e;
        *(uint4*)(sc->kv[1] + off) = v;
        if (tid < 16) *(uint4*)(sc->early[~ep & 1] + off) = make_uint4(0, 0, 0, 0);
        float n2 = bf_lo(v.x) * bf_lo(v.x) + bf_hi(v.x) * bf_hi(v.x) + bf_lo(v.y) * bf_lo(v.y) + bf_hi(v.y) * bf_hi(v.y) +
                   bf_lo(v.z) * bf_lo(v.z) + bf_hi(v.z) * bf_hi(v.z) + bf_lo(v.w) * bf_lo(v.w) + bf_hi(v.w) * bf_hi(v.w);
        n2 += __shfl_xor_sync(~0u, n2, 1);
        const uint32_t mx = __reduce_max_sync(~0u, __float_as_uint(n2) & 0x7FFFFFFFu);
        TL(55);
        if (lane == 0) {
          const uint32_t b = c == 0 ? mx : __uint_as_float(mx) <= 1e30f ? 0 : 0x7FFFFFFFu;
          asm volatile("red.relaxed.gpu.global.max.u64 [%0], %1;" ::"l"(sc->kvflag + 1), "l"(((unsigned long long)(ep + 1) << 32) | b) : "memory");
          asm volatile("red.release.gpu.global.add.u64 [%0], 1;" ::"l"(sc->kvflag) : "memory");
        }
        __syncwarp();
        TL(1);
      } else {
        bar_arrive(3, 512);
      }
      if ((lane & 3) == 0) {
        const uint32_t ad = SM_G + (warp * 16 + (lane >> 2)) * 4;
        sts32(ad, __float_as_uint(__fdividef(1.f, 1.f + __expf(-a[8]))));
        sts32(ad + 32, __float_as_uint(__fdividef(1.f, 1.f + __expf(-a[10]))));
      }
      mbar_wait(SM_QBAR, 0);
      if (QP) qv = lds128(SM_Q + tid * 16);
    } else {
      if (wid == 12) {
        TLW(26);
        mbar_wait(SM_XBAR + 0 * 8, 0);
        if (elect()) {
          sts32(SM_MAX + 4, ep + 1);
#pragma unroll 1
          for (int u = T >> 4; u < 7; u += 2) tma_prefetch(&maps.m[2 + ((T >> 3) & 1)], 448 * c + 64 * u, (T & 7) * 64);
        }
        __syncwarp();
#pragma unroll 1
        for (int i = 0; i < (1 << 21) && ld_relaxed((const unsigned int*)(sc->kvflag + 16)) != (ep + 1) << 8; i++) {}
        TLW(3);
      }
      bar_sync(3, 512);
      const unsigned char* src = sc->early[~lds32(SM_MAX + 4) & 1] + (tid - 128) * 16;
      uint4 v[3];
      v[2] = make_uint4(1, 1, 1, 1);
#pragma unroll
      for (int k = 0; k < 3; k++)
        if (k < 2 || wg < 3) v[k] = ld_relaxed4(src + k * 6144);
      if (CP) {
        uint32_t z = 0;
        if (wg == 3) {
#pragma unroll
          for (int i = 0; i < 5; i++) z |= (uint32_t)d.vv[i < 4 ? 8 * i : 31];
        } else if (wg == 1 && (CP & 2)) {
#pragma unroll
          for (int i = 0; i < 4; i++) z |= (uint32_t)d.xx[8 * i + 7] | (uint32_t)d.bb[i < 2 ? 8 * i : 15];
        }
        if (z == ~0u) __trap();
      }
      mbar_wait(SM_QBAR, 0);
      if (wg == 2) { TL(57); }
      if (QP) qv = lds128(SM_Q + tid * 16);
#pragma unroll 1
      for (int i = 0;; i++) {
        uint32_t z = ~0u;
#pragma unroll
        for (int k = 0; k < 3; k++) z = min(min(z, min(v[k].x, v[k].y)), min(v[k].z, v[k].w));
        if (__all_sync(~0u, z != 0)) break;
        if (i == (1 << 21)) __trap();
#pragma unroll
        for (int k = 0; k < 3; k++)
          if (k < 2 || wg < 3) v[k] = ld_relaxed4(src + k * 6144);
      }
#pragma unroll
      for (int k = 0; k < 3; k++) {
        const int i = tid - 128 + 384 * k;
        if (k < 2 || wg < 3) sts128(SM_KV + i * 16 + (i >> 9) * (KVS - KVB), make_uint4(~v[k].x, ~v[k].y, ~v[k].z, ~v[k].w));
      }
      fence_async_smem();
      __syncwarp();
      if (lane == 0) mbar_arrive(SM_SBAR);
      if (wg == 2) { TL(50); }
    }
    if (wg == 0) { TL(2); }
    const int duty = wg == warp ? wg : -1;
    auto finish = [&](int pass, const float* o) {
      int tid;
      asm volatile("mov.u32 %0, %%tid.x;" : "=r"(tid));
      const int warp = (tid >> 5) & 3, wg = tid >> 7;
      const uint32_t ga = SM_G + (warp * 16 + (lane >> 2)) * 4;
      const float l0 = __shfl_sync(~0u, o[8], lane & ~3), l1 = __shfl_sync(~0u, o[10], lane & ~3);
      const float r0 = __fdividef(ldsf(ga), l0), r1 = __fdividef(ldsf(ga + 32), l1);
      const uint32_t f0 = pack_bf16(o[0] * r0, o[1] * r0), f1 = pack_bf16(o[2] * r1, o[3] * r1);
      const uint32_t f2 = pack_bf16(o[4] * r0, o[5] * r0), f3 = pack_bf16(o[6] * r1, o[7] * r1);
      if (pass == 0) {
        uint32_t* op = (uint32_t*)(sc->o + bid * 8192 + wg * 2048 + warp * 256) + lane;
        op[0] = f0, op[32] = f1, op[256] = f2, op[288] = f3;
        TL(4 + wg * 2);
      } else {
        unsigned char* ex = sc->ex + T * 32768 + tid * 16;
        mbar_wait(SM_FBAR, 0);
        asm volatile("st.relaxed.gpu.global.v4.u32 [%0], {%1,%2,%3,%4};" ::"l"(ex + c * 8192), "r"(f0), "r"(f1), "r"(f2), "r"(f3) : "memory");
        TL(5 + wg * 2);
        const uint32_t ad = SM_X + 32768 + wg * 2048 + (lane >> 4) * 1024 + warp * 256 + (lane & 15) * 16;
        stsm4(ad + c * 8192, f0, f1, f2, f3);
        uint4 v[3];
        bool ok = false;
#pragma unroll 1
        for (int i = 0; i < (1 << 21) && !ok; i++) {
          uint32_t m = 0;
#pragma unroll
          for (int j = 0; j < 3; j++) {
            asm volatile("ld.relaxed.gpu.global.v4.u32 {%0,%1,%2,%3}, [%4];" : "=r"(v[j].x), "=r"(v[j].y), "=r"(v[j].z), "=r"(v[j].w)
                         : "l"(ex + ((c + 1 + j) & 3) * 8192) : "memory");
          }
#pragma unroll
          for (int j = 0; j < 3; j++) m = max(max(m, max(v[j].x, v[j].y)), max(v[j].z, v[j].w));
          ok = __all_sync(~0u, m != ~0u);
        }
        if (!ok) __trap();
#pragma unroll
        for (int j = 0; j < 3; j++) stsm4(ad + ((c + 1 + j) & 3) * 8192, v[j].x, v[j].y, v[j].z, v[j].w);
        fence_async_smem();
        __syncwarp();
        if (lane == 0) mbar_arrive(SM_OBAR + wg * 8);
        if (wg == 3) { TL(30); }
      }
    };
    bool fast = true;
    if (CR) asm volatile("{.reg .u32 t;\nmov.u32 t, %%warpid;\nshr.u32 t, t, 16;\nadd.u32 %0, %0, t;}" : "+r"(cor));
#pragma unroll 1
    for (int pass = 0; pass < 2; pass++) {
      float o[12];
      attn_fast(pass, duty, sc->kv[0], sc->flag + bid * 32, cor, d, qv, o);
      if (QP) qv = lds128(SM_Q + 8192 + tid * 16);
      const float qm = ldsf(SM_MAX), km = ldsf(SM_KM + 8);
      fast = __all_sync(~0u, qm * km * (QSCALE * QSCALE) <= 48.f * 48.f && qm <= 1048576.f && km <= 1048576.f);
      if (!fast) break;
      finish(pass, o);
    }
    if (!fast) {
      bar_sync(2, 512);
      if (tid == 384) {
#pragma unroll
        for (int i = 0; i < 2; i++) {
          mbar_wait(SM_KBAR + i * 8, 0);
          mbar_arrive(SM_KBAR + 16 + i * 8);
          mbar_expect(SM_KBAR + i * 8, KVB);
          bulk_g2s(SM_KV + i * KVS, sc->kv[1] + i * KVB, KVB, SM_KBAR + i * 8);
        }
      }
      bar_sync(2, 512);
#pragma unroll 1
      for (int pass = 0; pass < 2; pass++) {
        float o[12];
        attn_safe(pass, duty, sc->kv[1], sc->flag + bid * 32, d, o);
        finish(pass, o);
      }
    }
  }
}

typedef CUresult (*EncodeFn)(CUtensorMap*, CUtensorMapDataType, cuuint32_t, void*, const cuuint64_t*, const cuuint64_t*,
                             const cuuint32_t*, const cuuint32_t*, CUtensorMapInterleave, CUtensorMapSwizzle,
                             CUtensorMapL2promotion, CUtensorMapFloatOOBfill);

void make_map(EncodeFn fn, CUtensorMap* m, void* p, int rank, int rows, int cols, int box_rows) {
  cuuint64_t dims[3] = {(cuuint64_t)(rank == 2 ? cols : 64), (cuuint64_t)rows, (cuuint64_t)cols / 64};
  cuuint64_t strides[2] = {(cuuint64_t)cols * 2, 128};
  cuuint32_t box[3] = {64, (cuuint32_t)box_rows, 2};
  cuuint32_t es[3] = {1, 1, 1};
  fn(m, CU_TENSOR_MAP_DATA_TYPE_BFLOAT16, rank, p, dims, strides, box, es, CU_TENSOR_MAP_INTERLEAVE_NONE,
     CU_TENSOR_MAP_SWIZZLE_128B, CU_TENSOR_MAP_L2_PROMOTION_L2_128B, CU_TENSOR_MAP_FLOAT_OOB_FILL_NONE);
}

}

extern "C" void kernel_launch(void* const* d_in, const int* in_sizes, int n_in, void* d_out, int out_size) {
  static EncodeFn fn = nullptr;
  static Scratch* sc = nullptr;
  if (!fn) {
    void* p = nullptr;
    cudaDriverEntryPointQueryResult st;
    cudaGetDriverEntryPoint("cuTensorMapEncodeTiled", &p, cudaEnableDefault, &st);
    fn = (EncodeFn)p;
    cudaFuncSetAttribute(fused_kernel, cudaFuncAttributeMaxDynamicSharedMemorySize, SM_TOTAL);
    cudaGetSymbolAddress((void**)&sc, g_scratch);
  }
  Maps maps;
  make_map(fn, &maps.m[0], d_in[0], 3, 2048, 512, 64);
  make_map(fn, &maps.m[1], d_in[1], 3, 512, 512, 64);
  make_map(fn, &maps.m[2], d_in[6], 2, 512, 1792, 64);
  make_map(fn, &maps.m[3], d_in[7], 2, 512, 1792, 64);
  make_map(fn, &maps.m[4], d_in[8], 3, 1792, 512, 64);
  make_map(fn, &maps.m[5], d_in[4], 3, 512, 512, 64);
  Descs d{mkdesc(SM_KV, 128, 256, 0), mkdesc(SM_KV + 4096, 128, 2048, 0), mkdesc(SM_X, 16, 1024, 1),
                mkdesc(SM_X, 1024, 128, 0), mkdesc(SM_B, 8192, 1024, 1)};
  for (int h = 0; h < 32; h++) d.kk[h >> 2] = d.k + off_k(h >> 2), d.vv[h] = d.v + off_v(h >> 2) + (h & 3) * 16;
  for (int h = 0; h < 32; h++) d.xx[h] = d.x + (h >> 2) * 512 + (h & 3) * 2, d.aa[h] = d.a + h * 128;
  for (int h = 0; h < 24; h++) d.bb[h] = d.b + (h >> 2) * 1024 + (h & 3) * 128;
  fused_kernel<<<128, 640, SM_TOTAL>>>(sc, (const __nv_bfloat16*)d_in[2], (const __nv_bfloat16*)d_in[3],
                                       (const unsigned short*)d_in[9], (const unsigned char*)d_in[0], (const unsigned char*)d_in[1],
                                       (const unsigned char*)d_in[8], (const unsigned char*)d_in[4], (uint4*)d_out, 0x9F809F80u, d, maps);
}
```
